```python
import torch

def _softmax(x, axis=-1):
    return torch.softmax(x, dim=axis)
def _gelu(x):
    return torch.nn.functional.gelu(x, approximate="tanh")
def _silu(x):
    return torch.nn.functional.silu(x)
def _sigmoid(x):
    return torch.sigmoid(x)
def _layernorm(x, axis=-1, eps=1e-5):
    m = x.mean(dim=axis, keepdim=True)
    v = x.var(dim=axis, keepdim=True, unbiased=False)
    return (x - m) / torch.sqrt(v + eps)
def _scatter_add(tgt, idx, src, axis=0):
    return tgt.clone().index_add_(axis, idx, src)
def _segment_sum(src, seg, n):
    out = torch.zeros((n,) + src.shape[1:], dtype=src.dtype)
    return out.index_add_(0, seg, src)
def _pad(x, pw):
    flat = tuple(v for pair in reversed(pw) for v in pair)
    return torch.nn.functional.pad(x, flat)

kernel_name = 'recurrent_scan__mha_block_cached__dense_activation_silu__decode'

def setup_inputs():

    _w = (lambda a: (lambda t: t.to(torch.bfloat16) if t.is_floating_point() else t)(torch.as_tensor(a)))
    def _A_setup():
        B, Sq, D = 4, 1, 512
        H, Sk, Dh = 32, 8192, 128
        return {
            "x": _w((lambda *s: torch.randn(*s, dtype=torch.bfloat16) * 0.4)(B, Sq, D)),
            "k_cache": _w((lambda *s: torch.randn(*s, dtype=torch.bfloat16) * 1.6)(B, H, Sk, Dh)),
            "v_cache": _w((lambda *s: torch.randn(*s, dtype=torch.bfloat16) * 1.6)(B, H, Sk, Dh)),
            "wq": _w((lambda *s: torch.randn(*s, dtype=torch.bfloat16) * 1.6)(D, H * Dh) * (D ** -0.5)),
            "wo": _w((lambda *s: torch.randn(*s, dtype=torch.bfloat16) * 1.6)(H * Dh, D) * ((H * Dh) ** -0.5)),
        }
    _A_in = _A_setup()

    def _B_setup():
        B, S, D, F = 4, 1, 512, 1376
        return {
            "x": _w((lambda *s: torch.randn(*s, dtype=torch.bfloat16) * 0.4)(B, S, D)),
            "w1": _w((lambda *s: torch.randn(*s, dtype=torch.bfloat16) * 1.6)(D, F) * (D ** -0.5)),
            "w2": _w((lambda *s: torch.randn(*s, dtype=torch.bfloat16) * 1.6)(F, D) * (F ** -0.5)),
        }
    _B_in = _B_setup()

    return {
        "A_x": _A_in["x"],
        "A_k_cache": _A_in["k_cache"],
        "A_v_cache": _A_in["v_cache"],
        "A_wq": _A_in["wq"],
        "A_wo": _A_in["wo"],
        "B_x": _B_in["x"],
        "B_w1": _B_in["w1"],
        "B_w2": _B_in["w2"],
    }

def reference(A_x, A_k_cache, A_v_cache, A_wq, A_wo, B_x, B_w1, B_w2):
    def _A_ref(x, k_cache, v_cache, wq, wo):
        B, Sq, D = x.shape
        H, Dh = 32, 128
        q = (lambda x, *d: x.permute(*d))((x @ wq).reshape(B, Sq, H, Dh), 0, 2, 1, 3)
        scores = torch.einsum("bhqd,bhkd->bhqk", q, k_cache) * (Dh ** -0.5)
        p = _softmax(scores, axis=-1)
        o = torch.einsum("bhqk,bhkd->bhqd", p, v_cache)
        return (lambda x, *d: x.permute(*d))(o, 0, 2, 1, 3).reshape(B, Sq, H * Dh) @ wo

    def _B_ref(x, w1, w2):
        h = torch.einsum("bsd,df->bsf", x, w1)
        h = _silu(h)
        out = torch.einsum("bsf,fd->bsd", h, w2)
        return out

    x = A_x
    xn = _layernorm(x, axis=-1)
    s = _A_ref(xn, A_k_cache, A_v_cache, A_wq, A_wo)
    g = _silu(_B_ref(xn, B_w1, B_w2))
    return x + s * g
```

```cpp
#include <cuda_runtime.h>
#include <cuda.h>
#include <cuda_bf16.h>
#include <stdint.h>

namespace {

constexpr int NB = 4, DM = 512, NH = 32, SK = 8192, DH = 128, FF = 1376;
constexpr int NATT = NB * NH;
constexpr int NFFN = 4;
constexpr int NCTA = NATT + NFFN;
constexpr int NTHREADS = 416;

constexpr int TILE = 64;
constexpr int SLOT_BYTES = TILE * DH * 2;
#define KVTRIG 0
#define PACE 0
#define KNSLOT 4
constexpr int NSLOT = KNSLOT;
constexpr int NSTAGE = SK / TILE;
constexpr int NSEQ = 2 * NSTAGE;
constexpr int RING_BYTES = 6 * SLOT_BYTES;
constexpr int WO_BYTES = DH * DM * 2;
constexpr int WO_PIECES = 8;
constexpr int WO_PIECE_BYTES = WO_BYTES / WO_PIECES;

constexpr int OFF_WO = RING_BYTES;
constexpr int OFF_WQ = OFF_WO;
constexpr int WQ_BYTES = DM * 128;
constexpr int OFF_XS = OFF_WO + WQ_BYTES;
constexpr int OFF_MISC = OFF_WO + WO_BYTES;
constexpr int OFF_OCOMB = OFF_MISC;
constexpr int OFF_ML = OFF_OCOMB + 2048;
constexpr int OFF_OBF = OFF_ML + 32;
constexpr int OFF_QBF = OFF_OBF + 256;
constexpr int OFF_GATE = OFF_QBF + 256;
constexpr int OFF_BAR = OFF_GATE + 128;
constexpr int SMEM_BYTES = OFF_BAR + 160;
static_assert(SMEM_BYTES <= 232448, "smem");

constexpr int FSL = FF / NFFN;
constexpr int FOFF_XN = 0;
constexpr int FOFF_HP = 8192;
constexpr int FOFF_HS = FOFF_HP + 8 * 4 * FSL * 4;
constexpr int FOFF_OP = FOFF_HS + FSL * 16;

struct __align__(16) Word2 { unsigned long long a, b; };

__device__ unsigned int g_epoch[NCTA];
__device__ Word2 g_ox[NB][32][NH][8];
__device__ Word2 g_fx[NFFN][NB][32][8];

#define STAMP(i)
#define STAMP_SMID(i)
#define RSTAMP(v)
#define RFLUSH(i, v)

__device__ __forceinline__ uint32_t smem_u32(const void* p) { return (uint32_t)__cvta_generic_to_shared(p); }

__device__ __forceinline__ void mbar_init(uint32_t bar, uint32_t count) {
    asm volatile("mbarrier.init.shared::cta.b64 [%0], %1;" ::"r"(bar), "r"(count) : "memory");
}
__device__ __forceinline__ void mbar_expect_tx(uint32_t bar, uint32_t bytes) {
    asm volatile("mbarrier.arrive.expect_tx.shared::cta.b64 _, [%0], %1;" ::"r"(bar), "r"(bytes) : "memory");
}
__device__ __forceinline__ void mbar_arrive(uint32_t bar) {
    asm volatile("mbarrier.arrive.shared::cta.b64 _, [%0];" ::"r"(bar) : "memory");
}
__device__ __forceinline__ bool mbar_try(uint32_t bar, uint32_t parity) {
    uint32_t ok;
    asm volatile("{\n.reg .pred p;\nmbarrier.try_wait.parity.shared::cta.b64 p, [%1], %2;\nselp.u32 %0, 1, 0, p;\n}"
                 : "=r"(ok) : "r"(bar), "r"(parity) : "memory");
    return ok != 0;
}
constexpr long long SPIN_LIMIT_CLK = 4000000000LL;
__device__ __forceinline__ void mbar_wait(uint32_t bar, uint32_t parity) {
    if (mbar_try(bar, parity)) return;
    long long t0 = clock64();
    while (!mbar_try(bar, parity)) {
        if (clock64() - t0 > SPIN_LIMIT_CLK) __trap();
    }
}
__device__ __forceinline__ void bulk_load(uint32_t dst, const void* src, uint32_t bytes, uint32_t bar, uint64_t pol) {
    asm volatile("cp.async.bulk.shared::cluster.global.mbarrier::complete_tx::bytes.L2::cache_hint [%0], [%1], %2, [%3], %4;"
                 ::"r"(dst), "l"(src), "r"(bytes), "r"(bar), "l"(pol) : "memory");
}
__device__ __forceinline__ void bulk_load_nohint(uint32_t dst, const void* src, uint32_t bytes, uint32_t bar) {
    asm volatile("cp.async.bulk.shared::cluster.global.mbarrier::complete_tx::bytes [%0], [%1], %2, [%3];"
                 ::"r"(dst), "l"(src), "r"(bytes), "r"(bar) : "memory");
}
__device__ __forceinline__ void tensor_load_2d(uint32_t dst, const CUtensorMap* tm, int c0, int c1, uint32_t bar) {
    asm volatile("cp.async.bulk.tensor.2d.shared::cluster.global.mbarrier::complete_tx::bytes [%0], [%1, {%3, %4}], [%2];"
                 ::"r"(dst), "l"(tm), "r"(bar), "r"(c0), "r"(c1) : "memory");
}
__device__ __forceinline__ void prefetch_l2(const void* src, uint32_t bytes) {
    asm volatile("cp.async.bulk.prefetch.L2.global [%0], %1;" ::"l"(src), "r"(bytes) : "memory");
}
__device__ __forceinline__ void named_sync(int id, int n) { asm volatile("bar.sync %0, %1;" ::"r"(id), "r"(n) : "memory"); }
__device__ __forceinline__ void named_arrive(int id, int n) { asm volatile("bar.arrive %0, %1;" ::"r"(id), "r"(n) : "memory"); }

__device__ __forceinline__ void cluster_arrive_relaxed() { asm volatile("barrier.cluster.arrive.relaxed.aligned;" ::: "memory"); }
__device__ __forceinline__ void cluster_wait() { asm volatile("barrier.cluster.wait.aligned;" ::: "memory"); }
__device__ __forceinline__ uint32_t mapa(uint32_t addr, uint32_t rank) {
    uint32_t r;
    asm("mapa.shared::cluster.u32 %0, %1, %2;" : "=r"(r) : "r"(addr), "r"(rank));
    return r;
}
__device__ __forceinline__ void st_async_u32(uint32_t addr, uint32_t v, uint32_t bar) {
    asm volatile("st.async.weak.shared::cluster.mbarrier::complete_tx::bytes.u32 [%0], %1, [%2];" ::"r"(addr), "r"(v), "r"(bar) : "memory");
}

__device__ __forceinline__ void ldsm4(uint32_t (&r)[4], uint32_t addr) {
    asm volatile("ldmatrix.sync.aligned.m8n8.x4.shared.b16 {%0,%1,%2,%3}, [%4];"
                 : "=r"(r[0]), "=r"(r[1]), "=r"(r[2]), "=r"(r[3]) : "r"(addr) : "memory");
}
__device__ __forceinline__ void ldsm4t(uint32_t (&r)[4], uint32_t addr) {
    asm volatile("ldmatrix.sync.aligned.m8n8.x4.trans.shared.b16 {%0,%1,%2,%3}, [%4];"
                 : "=r"(r[0]), "=r"(r[1]), "=r"(r[2]), "=r"(r[3]) : "r"(addr) : "memory");
}
__device__ __forceinline__ void mma16816(float (&c)[4], uint32_t a0, uint32_t a1, uint32_t a2, uint32_t a3, uint32_t b0, uint32_t b1) {
    asm volatile("mma.sync.aligned.m16n8k16.row.col.f32.bf16.bf16.f32 {%0,%1,%2,%3}, {%4,%5,%6,%7}, {%8,%9}, {%0,%1,%2,%3};"
                 : "+f"(c[0]), "+f"(c[1]), "+f"(c[2]), "+f"(c[3])
                 : "r"(a0), "r"(a1), "r"(a2), "r"(a3), "r"(b0), "r"(b1));
}
__device__ __forceinline__ uint32_t pack_bf16(float lo, float hi) {
    uint32_t r;
    asm("cvt.rn.bf16x2.f32 %0, %1, %2;" : "=r"(r) : "f"(hi), "f"(lo));
    return r;
}
__device__ __forceinline__ float bf_lo(uint32_t u) { return __uint_as_float(u << 16); }
__device__ __forceinline__ float bf_hi(uint32_t u) { return __uint_as_float(u & 0xffff0000u); }
__device__ __forceinline__ float bf16r(float x) { return __bfloat162float(__float2bfloat16_rn(x)); }
__device__ __forceinline__ float ex2(float x) {
    float y;
    asm("ex2.approx.ftz.f32 %0, %1;" : "=f"(y) : "f"(x));
    return y;
}
__device__ __forceinline__ float silu_f(float x) { return x / (1.0f + expf(-x)); }

__device__ __forceinline__ uint4 ldg_nc(const void* p) {
    uint4 v;
    asm volatile("ld.global.nc.L1::no_allocate.v4.u32 {%0,%1,%2,%3}, [%4];" : "=r"(v.x), "=r"(v.y), "=r"(v.z), "=r"(v.w) : "l"(p));
    return v;
}
__device__ __forceinline__ Word2 ld_word2(const Word2* p) {
    Word2 v;
    asm volatile("ld.relaxed.gpu.global.v2.b64 {%0,%1}, [%2];" : "=l"(v.a), "=l"(v.b) : "l"(p) : "memory");
    return v;
}
__device__ __forceinline__ void st_word2(Word2* p, unsigned long long a, unsigned long long b) {
    asm volatile("st.relaxed.gpu.global.v2.b64 [%0], {%1,%2};" ::"l"(p), "l"(a), "l"(b) : "memory");
}
__device__ __forceinline__ void st_word(unsigned long long* p, unsigned long long a) {
    asm volatile("st.relaxed.gpu.global.b64 [%0], %1;" ::"l"(p), "l"(a) : "memory");
}
__device__ __forceinline__ uint32_t ld_epoch(const unsigned int* p) {
    uint32_t v;
    asm volatile("ld.relaxed.gpu.global.u32 %0, [%1];" : "=r"(v) : "l"(p) : "memory");
    return v;
}
__device__ __forceinline__ unsigned long long mkword(uint32_t payload, uint32_t tag) {
    return ((unsigned long long)tag << 32) | payload;
}
__device__ __forceinline__ bool word2_ok(const Word2& w, uint32_t tag) {
    return (uint32_t)(w.a >> 32) == tag && (uint32_t)(w.b >> 32) == tag;
}
__device__ __forceinline__ Word2 poll_word2(const Word2* p, uint32_t tag, unsigned sleep_ns) {
    Word2 w = ld_word2(p);
    if (__all_sync(0xffffffffu, word2_ok(w, tag))) return w;
    long long t0 = clock64();
    while (true) {
        if (sleep_ns) __nanosleep(sleep_ns);
        w = ld_word2(p);
        if (__all_sync(0xffffffffu, word2_ok(w, tag))) return w;
        if (clock64() - t0 > SPIN_LIMIT_CLK) __trap();
    }
}

__device__ __forceinline__ void layernorm_row(const uint4 a, const uint4 b, float (&v)[16]) {
    v[0] = bf_lo(a.x); v[1] = bf_hi(a.x); v[2] = bf_lo(a.y); v[3] = bf_hi(a.y);
    v[4] = bf_lo(a.z); v[5] = bf_hi(a.z); v[6] = bf_lo(a.w); v[7] = bf_hi(a.w);
    v[8] = bf_lo(b.x); v[9] = bf_hi(b.x); v[10] = bf_lo(b.y); v[11] = bf_hi(b.y);
    v[12] = bf_lo(b.z); v[13] = bf_hi(b.z); v[14] = bf_lo(b.w); v[15] = bf_hi(b.w);
    float s = 0.f;
#pragma unroll
    for (int i = 0; i < 16; i++) s += v[i];
#pragma unroll
    for (int o = 16; o > 0; o >>= 1) s += __shfl_xor_sync(0xffffffffu, s, o);
    const float mean = s * (1.0f / DM);
    float q = 0.f;
#pragma unroll
    for (int i = 0; i < 16; i++) { float d = v[i] - mean; q += d * d; }
#pragma unroll
    for (int o = 16; o > 0; o >>= 1) q += __shfl_xor_sync(0xffffffffu, q, o);
    const float mb = bf16r(mean);
    const float vb = bf16r(q * (1.0f / DM));
    const float den = bf16r(sqrtf(bf16r(vb + 1e-5f)));
#pragma unroll
    for (int i = 0; i < 16; i++) v[i] = bf16r(bf16r(v[i] - mb) / den);
}

__device__ __forceinline__ void ffn_gemv(float (&acc)[4][8], const __nv_bfloat16* __restrict__ wp, int ld,
                                         const float4* act, int r0, int r1) {
    for (int r = r0; r < r1; r += 16) {
        uint4 w[16];
#pragma unroll
        for (int u = 0; u < 16; u++) w[u] = (r + u < r1) ? ldg_nc(wp + (size_t)(r + u) * ld) : make_uint4(0, 0, 0, 0);
#pragma unroll
        for (int u = 0; u < 16; u++) {
            const float4 xv = act[min(r + u, r1 - 1)];
            const float wf[8] = {bf_lo(w[u].x), bf_hi(w[u].x), bf_lo(w[u].y), bf_hi(w[u].y),
                                 bf_lo(w[u].z), bf_hi(w[u].z), bf_lo(w[u].w), bf_hi(w[u].w)};
#pragma unroll
            for (int e = 0; e < 8; e++) {
                acc[0][e] = fmaf(xv.x, wf[e], acc[0][e]); acc[1][e] = fmaf(xv.y, wf[e], acc[1][e]);
                acc[2][e] = fmaf(xv.z, wf[e], acc[2][e]); acc[3][e] = fmaf(xv.w, wf[e], acc[3][e]);
            }
        }
    }
}

__device__ __forceinline__ void ffn_cta(unsigned char* smem, int f, const __nv_bfloat16* __restrict__ x,
                                        const __nv_bfloat16* __restrict__ w1, const __nv_bfloat16* __restrict__ w2,
                                        unsigned int* epoch, Word2* fxp) {
    const int tid = threadIdx.x, warp = tid >> 5, lane = tid & 31;
    float* xn4 = reinterpret_cast<float*>(smem + FOFF_XN);
    float* hp = reinterpret_cast<float*>(smem + FOFF_HP);
    float4* hs = reinterpret_cast<float4*>(smem + FOFF_HS);
    float* op = reinterpret_cast<float*>(smem + FOFF_OP);

    const uint32_t tag = ld_epoch(epoch + blockIdx.x) + 1;
    if (warp < 4) {
        const uint4* xr = reinterpret_cast<const uint4*>(x + warp * DM);
        float v[16];
        layernorm_row(ldg_nc(xr + lane), ldg_nc(xr + 32 + lane), v);
#pragma unroll
        for (int i = 0; i < 16; i++) xn4[((i < 8) ? (lane * 8 + i) : (248 + lane * 8 + i)) * 4 + warp] = v[i];
    }
    __syncthreads();
    if (tid == 0) epoch[blockIdx.x] = tag;

    float acc[4][8];
    if (tid < 344) {
        const int cg = tid % 43, ks = tid / 43;
#pragma unroll
        for (int b = 0; b < 4; b++)
#pragma unroll
            for (int e = 0; e < 8; e++) acc[b][e] = 0.f;
        ffn_gemv(acc, w1 + f * FSL + cg * 8, FF, reinterpret_cast<const float4*>(xn4), ks * 64, ks * 64 + 64);
#pragma unroll
        for (int b = 0; b < 4; b++)
#pragma unroll
            for (int e = 0; e < 8; e++) hp[(ks * 4 + b) * FSL + cg * 8 + e] = acc[b][e];
    }
    __syncthreads();
    for (int i = tid; i < 4 * FSL; i += NTHREADS) {
        const int b = i / FSL, c = i % FSL;
        float s = 0.f;
#pragma unroll
        for (int ks = 0; ks < 8; ks++) s += hp[(ks * 4 + b) * FSL + c];
        reinterpret_cast<float*>(hs)[c * 4 + b] = bf16r(silu_f(bf16r(s)));
    }
    __syncthreads();
    if (tid < 384) {
        const int cg = tid & 63, ks = tid >> 6;
#pragma unroll
        for (int b = 0; b < 4; b++)
#pragma unroll
            for (int e = 0; e < 8; e++) acc[b][e] = 0.f;
        ffn_gemv(acc, w2 + (size_t)(f * FSL) * DM + cg * 8, DM, hs, ks * 58, min(ks * 58 + 58, FSL));
#pragma unroll
        for (int b = 0; b < 4; b++)
#pragma unroll
            for (int e = 0; e < 8; e++) op[(ks * 4 + b) * DM + cg * 8 + e] = acc[b][e];
    }
    __syncthreads();
    for (int i = tid; i < NB * 32 * 8; i += NTHREADS) {
        const int b = i >> 8, hh = (i >> 3) & 31, g = i & 7;
        const int c0 = hh * 16 + g;
        float s0 = 0.f, s1 = 0.f;
#pragma unroll
        for (int ks = 0; ks < 6; ks++) { s0 += op[(ks * 4 + b) * DM + c0]; s1 += op[(ks * 4 + b) * DM + c0 + 8]; }
        st_word2(fxp + ((f * NB + b) * 32 + hh) * 8 + g, mkword(__float_as_uint(s0), tag), mkword(__float_as_uint(s1), tag));
    }
    if (tid == 0) STAMP(6);
}

template <int NT>
__device__ __forceinline__ void diag_reduce(const float (&acc)[NT][4], float (&u)[2 * NT]) {
#pragma unroll
    for (int s = 0; s < NT; s++) {
        u[2 * s] = acc[s][0] + acc[s][3];
        u[2 * s + 1] = acc[s][2] + acc[s][1];
    }
#pragma unroll
    for (int L = 0; L < 2 * NT; L++)
        if (!(L & 2)) u[L] += __shfl_xor_sync(0xffffffffu, u[L ^ 2], 1);
#pragma unroll
    for (int L = 0; L < 2 * NT; L++)
        if (!(L & 6)) u[L] += __shfl_xor_sync(0xffffffffu, u[L ^ 4], 2);
}

__global__ void __cluster_dims__(2, 1, 1) __launch_bounds__(NTHREADS, 1)
fused_decode_kernel(const __grid_constant__ CUtensorMap wq_map, const __nv_bfloat16* __restrict__ x,
                    const __nv_bfloat16* __restrict__ kc, const __nv_bfloat16* __restrict__ vc,
                    const __nv_bfloat16* __restrict__ wo, const __nv_bfloat16* __restrict__ w1,
                    const __nv_bfloat16* __restrict__ w2, __nv_bfloat16* __restrict__ out,
                    unsigned int* __restrict__ epoch, Word2* __restrict__ oxp, Word2* __restrict__ fxp) {
    extern __shared__ __align__(1024) unsigned char smem[];
    const int tid = threadIdx.x, warp = tid >> 5, lane = tid & 31;

    if (blockIdx.x >= NATT) {
        ffn_cta(smem, blockIdx.x - NATT, x, w1, w2, epoch, fxp);
        return;
    }

    const int a_idx = blockIdx.x;
    const int rank = a_idx & 1, h = (a_idx >> 1) & 31, bp = a_idx >> 6;
    const int b = 2 * bp + rank, bh = b * NH + h;
    const uint32_t sbase = smem_u32(smem);
    const uint32_t bar_full = sbase + OFF_BAR;
    const uint32_t bar_empty = bar_full + 8 * NSLOT;
    const uint32_t bar_wo = bar_empty + 8 * NSLOT;
    const uint32_t bar_q = bar_wo + 8;
    const uint32_t bar_scr = bar_q + 8;
    const uint32_t bar_wq = bar_scr + 8;

    if (warp == 12) {
        const char* kp = reinterpret_cast<const char*>(kc) + (size_t)bh * SK * DH * 2;
        const char* vp = reinterpret_cast<const char*>(vc) + (size_t)bh * SK * DH * 2;
        uint64_t pol;
        asm volatile("createpolicy.fractional.L2::evict_first.b64 %0, 1.0;" : "=l"(pol));
        if (lane == 0) {
            RSTAMP(t0);
            for (int s = 0; s < NSLOT; s++) { mbar_init(bar_full + 8 * s, 1); mbar_init(bar_empty + 8 * s, 4); }
            mbar_init(bar_wo, 1);
            mbar_init(bar_q, 1);
            mbar_init(bar_scr, 4);
            mbar_init(bar_wq, 1);
            mbar_init(bar_wq + 8, 1);
            mbar_expect_tx(bar_q, 256);
            asm volatile("fence.mbarrier_init.release.cluster;" ::: "memory");
            RFLUSH(0, t0);
        }
        __syncwarp();
        cluster_arrive_relaxed();
        if (lane == 0) {
#pragma unroll
            for (int i = 0; i < 2; i++) {
                mbar_expect_tx(bar_wq + 8 * i, WQ_BYTES / 2);
                tensor_load_2d(sbase + OFF_WQ + i * (WQ_BYTES / 2), &wq_map, h * DH + rank * 64, i * 256, bar_wq + 8 * i);
            }
            RSTAMP(t9);
            for (int s = 0; s < NSLOT; s++) {
                mbar_expect_tx(bar_full + 8 * s, SLOT_BYTES);
                bulk_load(sbase + s * SLOT_BYTES, ((s & 1) ? vp : kp) + (size_t)(s >> 1) * SLOT_BYTES, SLOT_BYTES, bar_full + 8 * s, pol);
                if (PACE && (s & 1)) { long long tp = clock64(); while (clock64() - tp < PACE) {} }
            }
            RSTAMP(t8);
            RFLUSH(20, t9); RFLUSH(8, t8);
        }
        __syncwarp();
        const uint32_t tag = ld_epoch(epoch + blockIdx.x) + 1;
        cluster_wait();
        if (lane == 0) {
            const char* wop = reinterpret_cast<const char*>(wo) + (size_t)h * WO_BYTES;
            int slot = 0;
            uint32_t ph = 0;
            for (int seq = NSLOT; seq < NSEQ; seq++) {
                mbar_wait(bar_empty + 8 * slot, ph);
                mbar_expect_tx(bar_full + 8 * slot, SLOT_BYTES);
                bulk_load(sbase + slot * SLOT_BYTES, ((seq & 1) ? vp : kp) + (size_t)(seq >> 1) * SLOT_BYTES, SLOT_BYTES,
                          bar_full + 8 * slot, pol);
                if (seq >= 8 && seq < 8 + 2 * WO_PIECES && !(seq & 1)) {
                    const int p = (seq - 8) >> 1;
                    if (p == 0) { mbar_wait(bar_scr, 0); mbar_expect_tx(bar_wo, WO_BYTES); }
                    bulk_load_nohint(sbase + OFF_WO + p * WO_PIECE_BYTES, wop + p * WO_PIECE_BYTES, WO_PIECE_BYTES, bar_wo);
                }
                if (++slot == NSLOT) { slot = 0; ph ^= 1; }
            }
            STAMP(1);
        }
        __syncwarp();
        named_sync(5, 64);
        const float* gate = reinterpret_cast<const float*>(smem + OFF_GATE);
        const int g = lane & 7, hq = lane >> 3;
        const float g0 = gate[g], g1 = gate[g + 8], x0 = gate[16 + g], x1 = gate[24 + g];
        const Word2* src = oxp + ((b * 32 + h) * NH + hq) * 8 + g;
        Word2 w[8];
#pragma unroll
        for (int j = 0; j < 8; j++) w[j] = ld_word2(src + j * 32);
        {
            long long t0 = clock64();
            while (true) {
                bool ok = true;
#pragma unroll
                for (int j = 0; j < 8; j++) ok = ok && word2_ok(w[j], tag);
                if (__all_sync(0xffffffffu, ok)) break;
#pragma unroll
                for (int j = 0; j < 8; j++)
                    if (!word2_ok(w[j], tag)) w[j] = ld_word2(src + j * 32);
                if (clock64() - t0 > SPIN_LIMIT_CLK) __trap();
            }
        }
        float s0 = 0.f, s1 = 0.f;
#pragma unroll
        for (int j = 0; j < 8; j++) { s0 += __uint_as_float((uint32_t)w[j].a); s1 += __uint_as_float((uint32_t)w[j].b); }
        s0 += __shfl_xor_sync(0xffffffffu, s0, 8);  s1 += __shfl_xor_sync(0xffffffffu, s1, 8);
        s0 += __shfl_xor_sync(0xffffffffu, s0, 16); s1 += __shfl_xor_sync(0xffffffffu, s1, 16);
        if (lane < 8) {
            __nv_bfloat16* op = out + b * DM + h * 16 + g;
            op[0] = __float2bfloat16_rn(x0 + bf16r(bf16r(s0) * g0));
            op[8] = __float2bfloat16_rn(x1 + bf16r(bf16r(s1) * g1));
        }
        if (lane == 0) { epoch[blockIdx.x] = tag; STAMP(7); }
        return;
    }

    const int g = lane >> 2, t = lane & 3;
    const int mi = lane >> 3, r = lane & 7;
    float* ocomb = reinterpret_cast<float*>(smem + OFF_OCOMB);
    float* ml = reinterpret_cast<float*>(smem + OFF_ML);
    uint16_t* obf = reinterpret_cast<uint16_t*>(smem + OFF_OBF);

    if (warp < 4) {
        if (warp < 2) {
            const uint4* xr = reinterpret_cast<const uint4*>(x + (2 * bp + warp) * DM);
            const uint4 xa = ldg_nc(xr + lane), xb = ldg_nc(xr + 32 + lane);
            cluster_arrive_relaxed();
            RSTAMP(t10);
            float v[16];
            layernorm_row(xa, xb, v);
            uint32_t* xs = reinterpret_cast<uint32_t*>(smem + OFF_XS) + warp * (4 * 68);
#pragma unroll
            for (int j = 0; j < 4; j++) {
                xs[j * 68 + lane] = pack_bf16(v[2 * j], v[2 * j + 1]);
                xs[j * 68 + 32 + lane] = pack_bf16(v[8 + 2 * j], v[8 + 2 * j + 1]);
            }
            __syncwarp();
            named_arrive(1, 192);
            RSTAMP(t11);
            if (tid == 0) { RFLUSH(10, t10); RFLUSH(11, t11); }
        } else {
            cluster_arrive_relaxed();
        }
        cluster_wait();
        mbar_wait(bar_q, 0);
        RSTAMP(t2);
        const uint32_t* qbf = reinterpret_cast<const uint32_t*>(smem + OFF_QBF);
        uint32_t qf[16];
#pragma unroll
        for (int L = 0; L < 16; L++) qf[L] = qbf[((L & 8) | ((L & 7) ^ g)) * 4 + t];

        const uint32_t rowoff = (uint32_t)(warp * 16 + (mi >> 1) * 8 + r) * 256;
        uint32_t coff[4];
#pragma unroll
        for (int j = 0; j < 4; j++) coff[j] = rowoff + ((((mi & 1) ^ r) ^ (2 * j)) << 4);

        const bool valid = (t == (g >> 1));
        const bool odd = g & 1;
        const uint32_t sel0 = odd ? 0x1044u : 0x4410u, sel1 = odd ? 0x3244u : 0x4432u;
        const float NEG_INF = __int_as_float(0xff800000);
        const float SCALE = 0.08838834764831845f, LOG2E = 1.4426950408889634f;

        float acc[8][4];
#pragma unroll
        for (int s = 0; s < 8; s++) { acc[s][0] = 0.f; acc[s][1] = 0.f; acc[s][2] = 0.f; acc[s][3] = 0.f; }
        float m = NEG_INF, msub = 0.f, l = 0.f;
        int slot = 0;
        uint32_t ph = 0;

        for (int st = 0; st < NSTAGE; st++) {
            uint32_t a[8][4];
            const uint32_t kb = sbase + slot * SLOT_BYTES;
            mbar_wait(bar_full + 8 * slot, ph);
#pragma unroll
            for (int s = 0; s < 8; s++) ldsm4(a[s], kb + coff[s & 3] + (s >> 2) * 128);
            float c0[4] = {0.f, 0.f, 0.f, 0.f}, c1[4] = {0.f, 0.f, 0.f, 0.f};
#pragma unroll
            for (int s = 0; s < 8; s += 2) {
                mma16816(c0, a[s][0], a[s][2], a[s][1], a[s][3], qf[2 * s], qf[2 * s + 1]);
                mma16816(c1, a[s + 1][0], a[s + 1][2], a[s + 1][1], a[s + 1][3], qf[2 * s + 2], qf[2 * s + 3]);
            }
            __syncwarp();
            if (lane == 0) mbar_arrive(bar_empty + 8 * slot);
            if (++slot == NSLOT) { slot = 0; ph ^= 1; }

            float sa = odd ? (c0[1] + c1[1]) : (c0[0] + c1[0]);
            float sb = odd ? (c0[3] + c1[3]) : (c0[2] + c1[2]);
            uint32_t pr = pack_bf16(sa, sb);
            pr = pack_bf16(bf_lo(pr) * SCALE, bf_hi(pr) * SCALE);
            sa = valid ? bf_lo(pr) : NEG_INF;
            sb = valid ? bf_hi(pr) : NEG_INF;
            const float tmax = fmaxf(sa, sb);
            if (__any_sync(0xffffffffu, tmax > m)) {
                float nm = tmax;
#pragma unroll
                for (int o = 16; o > 0; o >>= 1) nm = fmaxf(nm, __shfl_xor_sync(0xffffffffu, nm, o));
                nm = fmaxf(nm, m);
                const float alpha = ex2((m - nm) * LOG2E);
#pragma unroll
                for (int s = 0; s < 8; s++) { acc[s][0] *= alpha; acc[s][1] *= alpha; acc[s][2] *= alpha; acc[s][3] *= alpha; }
                l *= alpha;
                m = nm; msub = nm;
            }
            const float pa = ex2((sa - msub) * LOG2E), pb = ex2((sb - msub) * LOG2E);
            l += pa + pb;
            const uint32_t pp = pack_bf16(pa, pb);
            const uint32_t b0 = __byte_perm(pp, 0, sel0), b1 = __byte_perm(pp, 0, sel1);

            const uint32_t vb = sbase + slot * SLOT_BYTES;
            mbar_wait(bar_full + 8 * slot, ph);
#pragma unroll
            for (int s = 0; s < 8; s++) ldsm4t(a[s], vb + coff[s & 3] + (s >> 2) * 128);
#pragma unroll
            for (int s = 0; s < 8; s++) mma16816(acc[s], a[s][0], a[s][1], a[s][2], a[s][3], b0, b1);
            __syncwarp();
            if (lane == 0) mbar_arrive(bar_empty + 8 * slot);
            if (++slot == NSLOT) { slot = 0; ph ^= 1; }
        }
        if (tid == 0) { STAMP(3); STAMP_SMID(9); }

#pragma unroll
        for (int o = 16; o > 0; o >>= 1) l += __shfl_xor_sync(0xffffffffu, l, o);
        float u[16];
        diag_reduce<8>(acc, u);
        {
            float* oc = ocomb + warp * 128 + g;
            oc[(2 * t) * 8] = u[0];
            oc[(2 * t + 1) * 8] = u[1];
            oc[(8 + 2 * t) * 8] = u[8];
            oc[(9 + 2 * t) * 8] = u[9];
        }
        if (lane == 0) { ml[warp * 2] = m; ml[warp * 2 + 1] = l; }
        named_sync(3, 128);
        {
            const float4 ml01 = *reinterpret_cast<const float4*>(ml), ml23 = *reinterpret_cast<const float4*>(ml + 4);
            const float M = fmaxf(fmaxf(ml01.x, ml01.z), fmaxf(ml23.x, ml23.z));
            const float e0 = ex2((ml01.x - M) * LOG2E), e1 = ex2((ml01.z - M) * LOG2E);
            const float e2 = ex2((ml23.x - M) * LOG2E), e3 = ex2((ml23.z - M) * LOG2E);
            const float L = e0 * ml01.y + e1 * ml01.w + e2 * ml23.y + e3 * ml23.w;
            const float o = (e0 * ocomb[tid] + e1 * ocomb[128 + tid] + e2 * ocomb[256 + tid] + e3 * ocomb[384 + tid]) / L;
            obf[(tid & 7) * 16 + (tid >> 4) * 2 + ((tid >> 3) & 1)] = __bfloat16_as_ushort(__float2bfloat16_rn(o));
        }
        __syncwarp();
        named_arrive(4, 384);
        if (tid == 0) STAMP(5);
        return;
    }

    const int hw = warp - 4;
    cluster_arrive_relaxed();
    const uint32_t tag = ld_epoch(epoch + blockIdx.x) + 1;
    cluster_wait();
    if (hw < 4) {
        const uint32_t abase = sbase + OFF_WQ + (uint32_t)((mi >> 1) * 8 + r) * 128 + (uint32_t)(((2 * hw + (mi & 1)) ^ r) << 4);
        const uint4* xs = reinterpret_cast<const uint4*>(smem + OFF_XS + ((g & 1) * 4 + t) * (68 * 4));
        float qa[4][4];
#pragma unroll
        for (int i = 0; i < 4; i++) { qa[i][0] = 0.f; qa[i][1] = 0.f; qa[i][2] = 0.f; qa[i][3] = 0.f; }
        named_sync(1, 192);
        RSTAMP(t12);
#pragma unroll
        for (int half = 0; half < 2; half++) {
            uint32_t xw[32];
#pragma unroll
            for (int i = 0; i < 8; i++) {
                const uint4 v = xs[half * 8 + i];
                xw[4 * i] = v.x; xw[4 * i + 1] = v.y; xw[4 * i + 2] = v.z; xw[4 * i + 3] = v.w;
            }
            mbar_wait(bar_wq + 8 * half, 0);
#pragma unroll
            for (int ks = 0; ks < 16; ks++) {
                uint32_t a[4];
                ldsm4t(a, abase + (half * 16 + ks) * 2048);
                mma16816(qa[ks & 3], a[0], a[1], a[2], a[3], xw[2 * ks], xw[2 * ks + 1]);
            }
        }
        RSTAMP(t13);
        const int ci = t;
        float v = 0.f;
#pragma unroll
        for (int i = 0; i < 4; i++) v = (ci == i) ? ((qa[0][i] + qa[1][i]) + (qa[2][i] + qa[3][i])) : v;
        const float vo = __shfl_xor_sync(0xffffffffu, v, 4);
        if (!(g & 1)) {
            const uint32_t dst = t & 1;
            const uint32_t word = (uint32_t)(rank * 32 + hw * 8 + (t >> 1) * 4 + (g >> 1));
            st_async_u32(mapa(sbase + OFF_QBF + word * 4, dst), pack_bf16(v, vo), mapa(bar_q, dst));
        }
        asm volatile("fence.proxy.async.shared::cta;" ::: "memory");
        __syncwarp();
        if (lane == 0) mbar_arrive(bar_scr);
        RSTAMP(t14);
        if (tid == 128) { RFLUSH(12, t12); RFLUSH(13, t13); RFLUSH(14, t14); }
    }
    if (hw == 0) {
        const int gg = lane & 7, f = lane >> 3;
        const Word2 w = poll_word2(fxp + ((f * NB + b) * 32 + h) * 8 + gg, tag, 500);
        float s0 = __uint_as_float((uint32_t)w.a), s1 = __uint_as_float((uint32_t)w.b);
        s0 += __shfl_xor_sync(0xffffffffu, s0, 8);  s1 += __shfl_xor_sync(0xffffffffu, s1, 8);
        s0 += __shfl_xor_sync(0xffffffffu, s0, 16); s1 += __shfl_xor_sync(0xffffffffu, s1, 16);
        if (lane < 8) {
            float* gate = reinterpret_cast<float*>(smem + OFF_GATE);
            gate[gg] = bf16r(silu_f(bf16r(s0)));
            gate[gg + 8] = bf16r(silu_f(bf16r(s1)));
            gate[16 + gg] = __bfloat162float(x[b * DM + h * 16 + gg]);
            gate[24 + gg] = __bfloat162float(x[b * DM + h * 16 + gg + 8]);
        }
        __syncwarp();
        named_arrive(5, 64);
        if (lane == 0) STAMP(6);
    }

    {
        const uint32_t base = sbase + OFF_WO + (uint32_t)((mi >> 1) * 8 + r) * 1024 + hw * 128;
        const uint32_t xo = (uint32_t)((mi & 1) ^ r) << 4;
        uint32_t wf[7][4][4];
        mbar_wait(bar_wo, 0);
#pragma unroll
        for (int kk = 0; kk < 7; kk++)
#pragma unroll
            for (int s = 0; s < 4; s++) ldsm4t(wf[kk][s], base + kk * 16384 + (xo ^ (s << 5)));
        const bool valid = (t == (g >> 1));
        const bool odd = g & 1;
        const uint32_t sel0 = valid ? (odd ? 0x1044u : 0x4410u) : 0x4444u, sel1 = valid ? (odd ? 0x3244u : 0x4432u) : 0x4444u;
        float pacc[4][4];
#pragma unroll
        for (int s = 0; s < 4; s++) { pacc[s][0] = 0.f; pacc[s][1] = 0.f; pacc[s][2] = 0.f; pacc[s][3] = 0.f; }

        named_sync(4, 384);
        const uint4 ow0 = *reinterpret_cast<const uint4*>(obf + g * 16);
        const uint32_t owa[4] = {ow0.x, ow0.y, ow0.z, ow0.w};
        {
            const uint32_t b0 = __byte_perm(owa[0], 0, sel0), b1 = __byte_perm(owa[0], 0, sel1);
#pragma unroll
            for (int s = 0; s < 4; s++) mma16816(pacc[s], wf[0][s][0], wf[0][s][1], wf[0][s][2], wf[0][s][3], b0, b1);
        }
        uint32_t w7[4][4];
#pragma unroll
        for (int s = 0; s < 4; s++) ldsm4t(w7[s], base + 7 * 16384 + (xo ^ (s << 5)));
        const uint4 ow1 = *reinterpret_cast<const uint4*>(obf + g * 16 + 8);
        const uint32_t owb[4] = {ow1.x, ow1.y, ow1.z, ow1.w};
#pragma unroll
        for (int kk = 1; kk < 7; kk++) {
            const uint32_t ow = kk < 4 ? owa[kk] : owb[kk - 4];
            const uint32_t b0 = __byte_perm(ow, 0, sel0), b1 = __byte_perm(ow, 0, sel1);
#pragma unroll
            for (int s = 0; s < 4; s++) mma16816(pacc[s], wf[kk][s][0], wf[kk][s][1], wf[kk][s][2], wf[kk][s][3], b0, b1);
        }
        {
            const uint32_t b0 = __byte_perm(owb[3], 0, sel0), b1 = __byte_perm(owb[3], 0, sel1);
#pragma unroll
            for (int s = 0; s < 4; s++) mma16816(pacc[s], w7[s][0], w7[s][1], w7[s][2], w7[s][3], b0, b1);
        }
        float u[8];
        diag_reduce<4>(pacc, u);
        st_word2(oxp + ((b * 32 + 4 * hw + t) * NH + h) * 8 + g, mkword(__float_as_uint(u[0]), tag), mkword(__float_as_uint(u[1]), tag));
        if (tid == 128) STAMP(4);
    }
}

}

extern "C" void kernel_launch(void* const* d_in, const int* in_sizes, int n_in, void* d_out, int out_size) {
    (void)in_sizes; (void)n_in; (void)out_size;
    const __nv_bfloat16* x = (const __nv_bfloat16*)d_in[0];
    const __nv_bfloat16* kc = (const __nv_bfloat16*)d_in[1];
    const __nv_bfloat16* vc = (const __nv_bfloat16*)d_in[2];
    const __nv_bfloat16* wq = (const __nv_bfloat16*)d_in[3];
    const __nv_bfloat16* wo = (const __nv_bfloat16*)d_in[4];
    const __nv_bfloat16* w1 = (const __nv_bfloat16*)d_in[6];
    const __nv_bfloat16* w2 = (const __nv_bfloat16*)d_in[7];
    typedef CUresult (*EncodeFn)(CUtensorMap*, CUtensorMapDataType, cuuint32_t, void*, const cuuint64_t*, const cuuint64_t*,
                                 const cuuint32_t*, const cuuint32_t*, CUtensorMapInterleave, CUtensorMapSwizzle,
                                 CUtensorMapL2promotion, CUtensorMapFloatOOBfill);
    static unsigned int* epoch = nullptr;
    static Word2 *oxp = nullptr, *fxp = nullptr;
    static EncodeFn encode = nullptr;
    if (!epoch) {
        cudaFuncSetAttribute(fused_decode_kernel, cudaFuncAttributeMaxDynamicSharedMemorySize, SMEM_BYTES);
        void* fn = nullptr;
        cudaDriverEntryPointQueryResult qr;
        cudaGetDriverEntryPoint("cuTensorMapEncodeTiled", &fn, cudaEnableDefault, &qr);
        encode = (EncodeFn)fn;
        cudaGetSymbolAddress((void**)&oxp, g_ox);
        cudaGetSymbolAddress((void**)&fxp, g_fx);
        cudaGetSymbolAddress((void**)&epoch, g_epoch);
    }
    CUtensorMap wq_map;
    const cuuint64_t gdim[2] = {(cuuint64_t)(NH * DH), (cuuint64_t)DM};
    const cuuint64_t gstride[1] = {(cuuint64_t)(NH * DH * 2)};
    const cuuint32_t box[2] = {64, 256}, estride[2] = {1, 1};
    encode(&wq_map, CU_TENSOR_MAP_DATA_TYPE_BFLOAT16, 2, (void*)wq, gdim, gstride, box, estride, CU_TENSOR_MAP_INTERLEAVE_NONE,
           CU_TENSOR_MAP_SWIZZLE_128B, CU_TENSOR_MAP_L2_PROMOTION_NONE, CU_TENSOR_MAP_FLOAT_OOB_FILL_NONE);
    fused_decode_kernel<<<NCTA, NTHREADS, SMEM_BYTES, cudaStreamPerThread>>>(wq_map, x, kc, vc, wo, w1, w2, (__nv_bfloat16*)d_out,
                                                                             epoch, oxp, fxp);
}
```

```cpp
#include <cuda_runtime.h>
#include <cuda.h>
#include <cuda_bf16.h>
#include <stdint.h>

namespace {

constexpr int NB = 4, DM = 512, NH = 32, SK = 8192, DH = 128, FF = 1376;
constexpr int NATT = NB * NH;
constexpr int NFFN = 4;
constexpr int NCTA = NATT + NFFN;
constexpr int NTHREADS = 416;

constexpr int TILE = 64;
constexpr int SLOT_BYTES = TILE * DH * 2;
constexpr int NSLOT = 6;
constexpr int WIN_BASE = 4, WIN_MIN = 1, WIN_MAX = NSLOT;
constexpr int WIN_P_SHIFT = 8;
constexpr int WIN_I_SHIFT = 4;
constexpr int NSTAGE = SK / TILE;
constexpr int NSEQ = 2 * NSTAGE;
constexpr int RING_BYTES = NSLOT * SLOT_BYTES;
constexpr int WO_BYTES = DH * DM * 2;
constexpr int WO_PIECES = 8;
constexpr int WO_PIECE_BYTES = WO_BYTES / WO_PIECES;

constexpr int OFF_WO = RING_BYTES;
constexpr int OFF_WQ = OFF_WO;
constexpr int WQ_BYTES = DM * 128;
constexpr int OFF_XS = OFF_WO + WQ_BYTES;
constexpr int OFF_MISC = OFF_WO + WO_BYTES;
constexpr int OFF_OB = OFF_MISC;
constexpr int OFF_ML = OFF_OB + 1280;
constexpr int OFF_QBF = OFF_ML + 32;
constexpr int OFF_GATE = OFF_QBF + 256;
constexpr int OFF_FIN = OFF_GATE + 128;
constexpr int OFF_BAR = OFF_FIN + 256;
constexpr int SMEM_BYTES = OFF_BAR + 160;
static_assert(SMEM_BYTES <= 232448, "smem");

constexpr int FSL = FF / NFFN;
constexpr int FOFF_XN = 0;
constexpr int FOFF_HP = 8192;
constexpr int FOFF_HS = FOFF_HP + 8 * 4 * FSL * 4;
constexpr int FOFF_OP = FOFF_HS + FSL * 16;

struct __align__(16) Word2 { unsigned long long a, b; };

__device__ unsigned int g_epoch[NCTA];
__device__ unsigned int g_prog[2];
__device__ uint4 g_ox[NB][32][NH][4];
__device__ Word2 g_fx[NFFN][NB][32][8];


__device__ __forceinline__ uint32_t smem_u32(const void* p) { return (uint32_t)__cvta_generic_to_shared(p); }

__device__ __forceinline__ void mbar_init(uint32_t bar, uint32_t count) {
    asm volatile("mbarrier.init.shared::cta.b64 [%0], %1;" ::"r"(bar), "r"(count) : "memory");
}
__device__ __forceinline__ void mbar_expect_tx(uint32_t bar, uint32_t bytes) {
    asm volatile("mbarrier.arrive.expect_tx.shared::cta.b64 _, [%0], %1;" ::"r"(bar), "r"(bytes) : "memory");
}
__device__ __forceinline__ void mbar_arrive(uint32_t bar) {
    asm volatile("mbarrier.arrive.shared::cta.b64 _, [%0];" ::"r"(bar) : "memory");
}
__device__ __forceinline__ bool mbar_try(uint32_t bar, uint32_t parity) {
    uint32_t ok;
    asm volatile("{\n.reg .pred p;\nmbarrier.try_wait.parity.shared::cta.b64 p, [%1], %2;\nselp.u32 %0, 1, 0, p;\n}"
                 : "=r"(ok) : "r"(bar), "r"(parity) : "memory");
    return ok != 0;
}
constexpr long long SPIN_LIMIT_CLK = 4000000000LL;
constexpr uint32_t SPIN_LIMIT_ITERS = 1u << 23;
__device__ __forceinline__ void mbar_wait(uint32_t bar, uint32_t parity) {
    if (mbar_try(bar, parity)) return;
    long long t0 = clock64();
    while (!mbar_try(bar, parity)) {
        if (clock64() - t0 > SPIN_LIMIT_CLK) __trap();
    }
}
__device__ __forceinline__ void bulk_load(uint32_t dst, const void* src, uint32_t bytes, uint32_t bar, uint64_t pol) {
    asm volatile("cp.async.bulk.shared::cluster.global.mbarrier::complete_tx::bytes.L2::cache_hint [%0], [%1], %2, [%3], %4;"
                 ::"r"(dst), "l"(src), "r"(bytes), "r"(bar), "l"(pol) : "memory");
}
__device__ __forceinline__ void tensor_load_2d(uint32_t dst, const CUtensorMap* tm, int c0, int c1, uint32_t bar) {
    asm volatile("cp.async.bulk.tensor.2d.shared::cluster.global.mbarrier::complete_tx::bytes [%0], [%1, {%3, %4}], [%2];"
                 ::"r"(dst), "l"(tm), "r"(bar), "r"(c0), "r"(c1) : "memory");
}
__device__ __forceinline__ void tensor_load_3d(uint32_t dst, const CUtensorMap* tm, int c0, int c1, int c2, uint32_t bar) {
    asm volatile("cp.async.bulk.tensor.3d.shared::cluster.global.mbarrier::complete_tx::bytes [%0], [%1, {%3, %4, %5}], [%2];"
                 ::"r"(dst), "l"(tm), "r"(bar), "r"(c0), "r"(c1), "r"(c2) : "memory");
}
__device__ __forceinline__ void named_sync(int id, int n) { asm volatile("bar.sync %0, %1;" ::"r"(id), "r"(n) : "memory"); }
__device__ __forceinline__ void named_arrive(int id, int n) { asm volatile("bar.arrive %0, %1;" ::"r"(id), "r"(n) : "memory"); }

__device__ __forceinline__ void cluster_arrive_relaxed() { asm volatile("barrier.cluster.arrive.relaxed.aligned;" ::: "memory"); }
__device__ __forceinline__ void cluster_wait() { asm volatile("barrier.cluster.wait.aligned;" ::: "memory"); }
__device__ __forceinline__ uint32_t mapa(uint32_t addr, uint32_t rank) {
    uint32_t r;
    asm("mapa.shared::cluster.u32 %0, %1, %2;" : "=r"(r) : "r"(addr), "r"(rank));
    return r;
}
__device__ __forceinline__ void st_async_u32(uint32_t addr, uint32_t v, uint32_t bar) {
    asm volatile("st.async.weak.shared::cluster.mbarrier::complete_tx::bytes.u32 [%0], %1, [%2];" ::"r"(addr), "r"(v), "r"(bar) : "memory");
}

__device__ __forceinline__ void ldsm4(uint32_t (&r)[4], uint32_t addr) {
    asm volatile("ldmatrix.sync.aligned.m8n8.x4.shared.b16 {%0,%1,%2,%3}, [%4];"
                 : "=r"(r[0]), "=r"(r[1]), "=r"(r[2]), "=r"(r[3]) : "r"(addr) : "memory");
}
__device__ __forceinline__ void ldsm4t(uint32_t (&r)[4], uint32_t addr) {
    asm volatile("ldmatrix.sync.aligned.m8n8.x4.trans.shared.b16 {%0,%1,%2,%3}, [%4];"
                 : "=r"(r[0]), "=r"(r[1]), "=r"(r[2]), "=r"(r[3]) : "r"(addr) : "memory");
}
__device__ __forceinline__ void mma16816(float (&c)[4], uint32_t a0, uint32_t a1, uint32_t a2, uint32_t a3, uint32_t b0, uint32_t b1) {
    asm volatile("mma.sync.aligned.m16n8k16.row.col.f32.bf16.bf16.f32 {%0,%1,%2,%3}, {%4,%5,%6,%7}, {%8,%9}, {%0,%1,%2,%3};"
                 : "+f"(c[0]), "+f"(c[1]), "+f"(c[2]), "+f"(c[3])
                 : "r"(a0), "r"(a1), "r"(a2), "r"(a3), "r"(b0), "r"(b1));
}
__device__ __forceinline__ uint32_t pack_bf16(float lo, float hi) {
    uint32_t r;
    asm("cvt.rn.bf16x2.f32 %0, %1, %2;" : "=r"(r) : "f"(hi), "f"(lo));
    return r;
}
__device__ __forceinline__ float bf_lo(uint32_t u) { return __uint_as_float(u << 16); }
__device__ __forceinline__ float bf_hi(uint32_t u) { return __uint_as_float(u & 0xffff0000u); }
__device__ __forceinline__ float bf16r(float x) { return __bfloat162float(__float2bfloat16_rn(x)); }
__device__ __forceinline__ float ex2(float x) {
    float y;
    asm("ex2.approx.ftz.f32 %0, %1;" : "=f"(y) : "f"(x));
    return y;
}
__device__ __forceinline__ float silu_f(float x) { return x / (1.0f + expf(-x)); }

__device__ __forceinline__ uint4 ldg_nc(const void* p) {
    uint4 v;
    asm volatile("ld.global.nc.L1::no_allocate.v4.u32 {%0,%1,%2,%3}, [%4];" : "=r"(v.x), "=r"(v.y), "=r"(v.z), "=r"(v.w) : "l"(p));
    return v;
}
__device__ __forceinline__ Word2 ld_word2(const Word2* p) {
    Word2 v;
    asm volatile("ld.relaxed.gpu.global.v2.b64 {%0,%1}, [%2];" : "=l"(v.a), "=l"(v.b) : "l"(p) : "memory");
    return v;
}
__device__ __forceinline__ void st_word2(Word2* p, unsigned long long a, unsigned long long b) {
    asm volatile("st.relaxed.gpu.global.v2.b64 [%0], {%1,%2};" ::"l"(p), "l"(a), "l"(b) : "memory");
}
__device__ __forceinline__ uint4 ld_relaxed_v4(const uint4* p) {
    uint4 v;
    asm volatile("ld.relaxed.gpu.global.v4.u32 {%0,%1,%2,%3}, [%4];" : "=r"(v.x), "=r"(v.y), "=r"(v.z), "=r"(v.w) : "l"(p) : "memory");
    return v;
}
__device__ __forceinline__ void st_relaxed_v2(uint2* p, uint32_t a, uint32_t b) {
    asm volatile("st.relaxed.gpu.global.v2.u32 [%0], {%1,%2};" ::"l"(p), "r"(a), "r"(b) : "memory");
}
template <typename T>
__device__ __forceinline__ T* late(T* p) { asm volatile("" : "+l"(p) :: "memory"); return p; }
__device__ __forceinline__ uint32_t ld_epoch(const unsigned int* p) {
    uint32_t v;
    asm volatile("ld.relaxed.gpu.global.u32 %0, [%1];" : "=r"(v) : "l"(p) : "memory");
    return v;
}
__device__ __forceinline__ unsigned long long mkword(uint32_t payload, uint32_t tag) {
    return ((unsigned long long)tag << 32) | payload;
}
__device__ __forceinline__ bool word2_ok(const Word2& w, uint32_t tag) {
    return (uint32_t)(w.a >> 32) == tag && (uint32_t)(w.b >> 32) == tag;
}
__device__ __forceinline__ Word2 poll_word2(const Word2* p, uint32_t tag, unsigned sleep_ns) {
    Word2 w = ld_word2(p);
    if (__all_sync(0xffffffffu, word2_ok(w, tag))) return w;
    long long t0 = clock64();
    while (true) {
        if (sleep_ns) __nanosleep(sleep_ns);
        w = ld_word2(p);
        if (__all_sync(0xffffffffu, word2_ok(w, tag))) return w;
        if (clock64() - t0 > SPIN_LIMIT_CLK) __trap();
    }
}

__device__ __forceinline__ void layernorm_row(const uint4 a, const uint4 b, float (&v)[16]) {
    v[0] = bf_lo(a.x); v[1] = bf_hi(a.x); v[2] = bf_lo(a.y); v[3] = bf_hi(a.y);
    v[4] = bf_lo(a.z); v[5] = bf_hi(a.z); v[6] = bf_lo(a.w); v[7] = bf_hi(a.w);
    v[8] = bf_lo(b.x); v[9] = bf_hi(b.x); v[10] = bf_lo(b.y); v[11] = bf_hi(b.y);
    v[12] = bf_lo(b.z); v[13] = bf_hi(b.z); v[14] = bf_lo(b.w); v[15] = bf_hi(b.w);
    float s = 0.f;
#pragma unroll
    for (int i = 0; i < 16; i++) s += v[i];
#pragma unroll
    for (int o = 16; o > 0; o >>= 1) s += __shfl_xor_sync(0xffffffffu, s, o);
    const float mean = s * (1.0f / DM);
    float q = 0.f;
#pragma unroll
    for (int i = 0; i < 16; i++) { float d = v[i] - mean; q += d * d; }
#pragma unroll
    for (int o = 16; o > 0; o >>= 1) q += __shfl_xor_sync(0xffffffffu, q, o);
    const float mb = bf16r(mean);
    const float vb = bf16r(q * (1.0f / DM));
    const float den = bf16r(sqrtf(bf16r(vb + 1e-5f)));
#pragma unroll
    for (int i = 0; i < 16; i++) v[i] = bf16r(bf16r(v[i] - mb) / den);
}

__device__ __forceinline__ void ffn_gemv(float (&acc)[4][8], const __nv_bfloat16* __restrict__ wp, int ld,
                                         const float4* act, int r0, int r1) {
    for (int r = r0; r < r1; r += 16) {
        uint4 w[16];
#pragma unroll
        for (int u = 0; u < 16; u++) w[u] = (r + u < r1) ? ldg_nc(wp + (size_t)(r + u) * ld) : make_uint4(0, 0, 0, 0);
#pragma unroll
        for (int u = 0; u < 16; u++) {
            const float4 xv = act[min(r + u, r1 - 1)];
            const float wf[8] = {bf_lo(w[u].x), bf_hi(w[u].x), bf_lo(w[u].y), bf_hi(w[u].y),
                                 bf_lo(w[u].z), bf_hi(w[u].z), bf_lo(w[u].w), bf_hi(w[u].w)};
#pragma unroll
            for (int e = 0; e < 8; e++) {
                acc[0][e] = fmaf(xv.x, wf[e], acc[0][e]); acc[1][e] = fmaf(xv.y, wf[e], acc[1][e]);
                acc[2][e] = fmaf(xv.z, wf[e], acc[2][e]); acc[3][e] = fmaf(xv.w, wf[e], acc[3][e]);
            }
        }
    }
}

__device__ __forceinline__ void ffn_cta(unsigned char* smem, int f, const __nv_bfloat16* __restrict__ x,
                                        const __nv_bfloat16* __restrict__ w1, const __nv_bfloat16* __restrict__ w2,
                                        unsigned int* epoch, Word2* fxp) {
    const int tid = threadIdx.x, warp = tid >> 5, lane = tid & 31;
    float* xn4 = reinterpret_cast<float*>(smem + FOFF_XN);
    float* hp = reinterpret_cast<float*>(smem + FOFF_HP);
    float4* hs = reinterpret_cast<float4*>(smem + FOFF_HS);
    float* op = reinterpret_cast<float*>(smem + FOFF_OP);

    const uint32_t tag = ld_epoch(epoch + blockIdx.x) + 1;
    if (warp < 4) {
        const uint4* xr = reinterpret_cast<const uint4*>(x + warp * DM);
        float v[16];
        layernorm_row(ldg_nc(xr + lane), ldg_nc(xr + 32 + lane), v);
#pragma unroll
        for (int i = 0; i < 16; i++) xn4[((i < 8) ? (lane * 8 + i) : (248 + lane * 8 + i)) * 4 + warp] = v[i];
    }
    __syncthreads();
    if (tid == 0) epoch[blockIdx.x] = tag;

    float acc[4][8];
    if (tid < 344) {
        const int cg = tid % 43, ks = tid / 43;
#pragma unroll
        for (int b = 0; b < 4; b++)
#pragma unroll
            for (int e = 0; e < 8; e++) acc[b][e] = 0.f;
        ffn_gemv(acc, w1 + f * FSL + cg * 8, FF, reinterpret_cast<const float4*>(xn4), ks * 64, ks * 64 + 64);
#pragma unroll
        for (int b = 0; b < 4; b++)
#pragma unroll
            for (int e = 0; e < 8; e++) hp[(ks * 4 + b) * FSL + cg * 8 + e] = acc[b][e];
    }
    __syncthreads();
    for (int i = tid; i < 4 * FSL; i += NTHREADS) {
        const int b = i / FSL, c = i % FSL;
        float s = 0.f;
#pragma unroll
        for (int ks = 0; ks < 8; ks++) s += hp[(ks * 4 + b) * FSL + c];
        reinterpret_cast<float*>(hs)[c * 4 + b] = bf16r(silu_f(bf16r(s)));
    }
    __syncthreads();
    if (tid < 384) {
        const int cg = tid & 63, ks = tid >> 6;
#pragma unroll
        for (int b = 0; b < 4; b++)
#pragma unroll
            for (int e = 0; e < 8; e++) acc[b][e] = 0.f;
        ffn_gemv(acc, w2 + (size_t)(f * FSL) * DM + cg * 8, DM, hs, ks * 58, min(ks * 58 + 58, FSL));
#pragma unroll
        for (int b = 0; b < 4; b++)
#pragma unroll
            for (int e = 0; e < 8; e++) op[(ks * 4 + b) * DM + cg * 8 + e] = acc[b][e];
    }
    __syncthreads();
    for (int i = tid; i < NB * 32 * 8; i += NTHREADS) {
        const int b = i >> 8, hh = (i >> 3) & 31, g = i & 7;
        const int c0 = hh * 16 + g;
        float s0 = 0.f, s1 = 0.f;
#pragma unroll
        for (int ks = 0; ks < 6; ks++) { s0 += op[(ks * 4 + b) * DM + c0]; s1 += op[(ks * 4 + b) * DM + c0 + 8]; }
        st_word2(fxp + ((f * NB + b) * 32 + hh) * 8 + g, mkword(__float_as_uint(s0), tag), mkword(__float_as_uint(s1), tag));
    }
}

template <int NT>
__device__ __forceinline__ void diag_reduce(const float (&acc)[NT][4], float (&u)[2 * NT]) {
#pragma unroll
    for (int s = 0; s < NT; s++) {
        u[2 * s] = acc[s][0] + acc[s][3];
        u[2 * s + 1] = acc[s][2] + acc[s][1];
    }
#pragma unroll
    for (int L = 0; L < 2 * NT; L++)
        if (!(L & 2)) u[L] += __shfl_xor_sync(0xffffffffu, u[L ^ 2], 1);
#pragma unroll
    for (int L = 0; L < 2 * NT; L++)
        if (!(L & 6)) u[L] += __shfl_xor_sync(0xffffffffu, u[L ^ 4], 2);
}

__device__ __forceinline__ float combine_stats(float m, float l, float* ml, int warp, int lane) {
    const float LOG2E = 1.4426950408889634f;
#pragma unroll
    for (int o = 16; o > 0; o >>= 1) l += __shfl_xor_sync(0xffffffffu, l, o);
    if (lane == 0) *reinterpret_cast<float2*>(ml + warp * 2) = make_float2(m, l);
    named_sync(3, 128);
    const float4 ml01 = *reinterpret_cast<const float4*>(ml), ml23 = *reinterpret_cast<const float4*>(ml + 4);
    const float M = fmaxf(fmaxf(ml01.x, ml01.z), fmaxf(ml23.x, ml23.z));
    const float L = ex2((ml01.x - M) * LOG2E) * ml01.y + ex2((ml01.z - M) * LOG2E) * ml01.w +
                    ex2((ml23.x - M) * LOG2E) * ml23.y + ex2((ml23.z - M) * LOG2E) * ml23.w;
    return ex2((m - M) * LOG2E) / L;
}

__device__ __forceinline__ void publish_partial(const float (&acc)[8][4], float cw, uint32_t* ob, int warp, int g, int t) {
    float u[16];
    diag_reduce<8>(acc, u);
    const bool og = g & 1;
    const float k0 = (og ? u[8] : u[0]) * cw, k1 = (og ? u[9] : u[1]) * cw;
    const float s0 = (og ? u[0] : u[8]) * cw, s1 = (og ? u[1] : u[9]) * cw;
    const float r0 = __shfl_xor_sync(0xffffffffu, s0, 4), r1 = __shfl_xor_sync(0xffffffffu, s1, 4);
    const uint32_t w0 = og ? pack_bf16(r0, k0) : pack_bf16(k0, r0);
    const uint32_t w1 = og ? pack_bf16(r1, k1) : pack_bf16(k1, r1);
    *reinterpret_cast<uint2*>(ob + warp * 80 + (g >> 1) * 20 + (og ? 8 : 0) + 2 * t) = make_uint2(w0, w1);
    __syncwarp();
}

__global__ void __cluster_dims__(2, 1, 1) __launch_bounds__(NTHREADS, 1)
fused_decode_kernel(const __nv_bfloat16* __restrict__ x, const __nv_bfloat16* __restrict__ kc,
                    const __nv_bfloat16* __restrict__ vc, __nv_bfloat16* __restrict__ out,
                    const __nv_bfloat16* __restrict__ w1, const __nv_bfloat16* __restrict__ w2,
                    unsigned int* __restrict__ epoch_, unsigned int* __restrict__ progp,
                    uint4* __restrict__ oxp, Word2* __restrict__ fxp,
                    const __grid_constant__ CUtensorMap wq_map, const __grid_constant__ CUtensorMap wo_map) {
    extern __shared__ __align__(1024) unsigned char smem[];
    const int tid = threadIdx.x, warp = tid >> 5, lane = tid & 31;

    if (blockIdx.x >= NATT) {
        ffn_cta(smem, blockIdx.x - NATT, x, w1, w2, epoch_, fxp);
        return;
    }

    const int a_idx = blockIdx.x;
    const int rank = a_idx & 1, h = (a_idx >> 1) & 31, bp = a_idx >> 6;
    const int b = 2 * bp + rank, bh = b * NH + h;
    const uint32_t sbase = smem_u32(smem);
    const uint32_t bar_full = sbase + OFF_BAR;
    const uint32_t bar_empty = bar_full + 8 * NSLOT;
    const uint32_t bar_wo = bar_empty + 8 * NSLOT;
    const uint32_t bar_q = bar_wo + 8;
    const uint32_t bar_scr = bar_q + 8;
    const uint32_t bar_wq = bar_scr + 8;

    if (warp == 12) {
        const char* kp = reinterpret_cast<const char*>(kc) + (size_t)bh * SK * DH * 2;
        const char* vp = reinterpret_cast<const char*>(vc) + (size_t)bh * SK * DH * 2;
        uint64_t pol;
        asm volatile("createpolicy.fractional.L2::evict_first.b64 %0, 1.0;" : "=l"(pol));
        if (lane == 0) {
            mbar_init(bar_wq, 1);
            mbar_init(bar_wq + 8, 1);
#pragma unroll
            for (int i = 0; i < 2; i++) {
                mbar_expect_tx(bar_wq + 8 * i, WQ_BYTES / 2);
                tensor_load_2d(sbase + OFF_WQ + i * (WQ_BYTES / 2), &wq_map, h * DH + rank * 64, i * 256, bar_wq + 8 * i);
            }
            for (int s = 0; s < NSLOT; s++) mbar_init(bar_full + 8 * s, 1);
            for (int s = 0; s < WIN_BASE; s++) {
                mbar_expect_tx(bar_full + 8 * s, SLOT_BYTES);
                bulk_load(sbase + s * SLOT_BYTES, ((s & 1) ? vp : kp) + (size_t)(s >> 1) * SLOT_BYTES, SLOT_BYTES, bar_full + 8 * s, pol);
            }
            for (int s = 0; s < NSLOT; s++) mbar_init(bar_empty + 8 * s, 4);
            mbar_init(bar_wo, 1);
            mbar_init(bar_q, 1);
            mbar_init(bar_scr, 4);
            mbar_expect_tx(bar_q, 256);
            asm volatile("fence.mbarrier_init.release.cluster;" ::: "memory");
            asm volatile("prefetch.tensormap [%0];" ::"l"(&wo_map) : "memory");
        }
        __syncwarp();
        cluster_arrive_relaxed();
        unsigned int* epoch = late(epoch_);
        const uint32_t tag = ld_epoch(epoch + blockIdx.x) + 1;
        cluster_wait();
        if (lane == 0) {
            unsigned int* prog = progp + (tag & 1);
            if (blockIdx.x == 0) progp[(tag + 1) & 1] = 0;
            int win = WIN_BASE, integ = 0, nupd = 0;
            uint32_t pend = 0;
            int slot = WIN_BASE % NSLOT;
            for (int seq = WIN_BASE; seq < NSEQ; seq++) {
                if (!(seq & 1)) {
                    if (nupd > 0) {
                        int ctl = (int)(2 * pend) - 2 * (nupd - 1) * NATT - 128;
                        integ = min(max(integ + ctl, -(3 << (WIN_P_SHIFT + WIN_I_SHIFT))), 3 << (WIN_P_SHIFT + WIN_I_SHIFT));
                        ctl += (integ >> WIN_I_SHIFT) + 32 + 64 * (nupd & 3);
                        win = min(max(WIN_BASE + (ctl >> WIN_P_SHIFT), WIN_MIN), WIN_MAX);
                    }
                    pend = atomicAdd(prog, 1u);
                    nupd++;
                }
                const int j = seq - win;
                if (j >= 0) mbar_wait(bar_empty + 8 * (j % NSLOT), (j / NSLOT) & 1);
                mbar_expect_tx(bar_full + 8 * slot, SLOT_BYTES);
                bulk_load(sbase + slot * SLOT_BYTES, ((seq & 1) ? vp : kp) + (size_t)(seq >> 1) * SLOT_BYTES, SLOT_BYTES,
                          bar_full + 8 * slot, pol);
                if (seq >= 8 && seq < 8 + 2 * WO_PIECES && !(seq & 1)) {
                    const int p = (seq - 8) >> 1;
                    if (p == 0) { mbar_wait(bar_scr, 0); mbar_expect_tx(bar_wo, WO_BYTES); }
                    tensor_load_3d(sbase + OFF_WO + p * WO_PIECE_BYTES, &wo_map, 0, h * DH + p * 16, 0, bar_wo);
                }
                if (++slot == NSLOT) slot = 0;
            }
            epoch[blockIdx.x] = tag;
        }
        return;
    }

    const int g = lane >> 2, t = lane & 3;
    const int mi = lane >> 3, r = lane & 7;
    uint32_t* ob = reinterpret_cast<uint32_t*>(smem + OFF_OB);

    if (warp < 4) {
        if (warp < 2) {
            const uint4* xr = reinterpret_cast<const uint4*>(x + (2 * bp + warp) * DM);
            const uint4 xa = ldg_nc(xr + lane), xb = ldg_nc(xr + 32 + lane);
            cluster_arrive_relaxed();
            float v[16];
            layernorm_row(xa, xb, v);
            uint32_t* xs = reinterpret_cast<uint32_t*>(smem + OFF_XS) + warp * (4 * 68);
#pragma unroll
            for (int j = 0; j < 4; j++) {
                xs[j * 68 + lane] = pack_bf16(v[2 * j], v[2 * j + 1]);
                xs[j * 68 + 32 + lane] = pack_bf16(v[8 + 2 * j], v[8 + 2 * j + 1]);
            }
            __syncwarp();
            named_arrive(1, 192);
        } else {
            cluster_arrive_relaxed();
        }
        const uint32_t tag = ld_epoch(late(epoch_) + blockIdx.x) + 1;
        cluster_wait();
        mbar_wait(bar_q, 0);
        const uint32_t* qbf = reinterpret_cast<const uint32_t*>(smem + OFF_QBF);
        uint32_t qf[16];
#pragma unroll
        for (int L = 0; L < 16; L++) qf[L] = qbf[((L & 8) | ((L & 7) ^ g)) * 4 + t];

        const uint32_t rowoff = (uint32_t)(warp * 16 + (mi >> 1) * 8 + r) * 256;
        uint32_t coff[4];
#pragma unroll
        for (int j = 0; j < 4; j++) coff[j] = rowoff + ((((mi & 1) ^ r) ^ (2 * j)) << 4);

        const bool valid = (t == (g >> 1));
        const bool odd = g & 1;
        const uint32_t sel0 = odd ? 0x1044u : 0x4410u, sel1 = odd ? 0x3244u : 0x4432u;
        const float NEG_INF = __int_as_float(0xff800000);
        const float SCALE = 0.08838834764831845f, LOG2E = 1.4426950408889634f;

        float acc[8][4];
#pragma unroll
        for (int s = 0; s < 8; s++) { acc[s][0] = 0.f; acc[s][1] = 0.f; acc[s][2] = 0.f; acc[s][3] = 0.f; }
        float m = NEG_INF, msub = 0.f, l = 0.f, cw = 0.f;
        float* ml = reinterpret_cast<float*>(smem + OFF_ML);
        int slot = 0;
        uint32_t ph = 0;

        for (int st = 0; st < NSTAGE; st++) {
            uint32_t a[8][4];
            const uint32_t kb = sbase + slot * SLOT_BYTES;
            mbar_wait(bar_full + 8 * slot, ph);
#pragma unroll
            for (int s = 0; s < 8; s++) ldsm4(a[s], kb + coff[s & 3] + (s >> 2) * 128);
            float c0[4] = {0.f, 0.f, 0.f, 0.f}, c1[4] = {0.f, 0.f, 0.f, 0.f};
#pragma unroll
            for (int s = 0; s < 8; s += 2) {
                mma16816(c0, a[s][0], a[s][2], a[s][1], a[s][3], qf[2 * s], qf[2 * s + 1]);
                mma16816(c1, a[s + 1][0], a[s + 1][2], a[s + 1][1], a[s + 1][3], qf[2 * s + 2], qf[2 * s + 3]);
            }
            __syncwarp();
            if (lane == 0) mbar_arrive(bar_empty + 8 * slot);
            if (++slot == NSLOT) { slot = 0; ph ^= 1; }

            float sa = odd ? (c0[1] + c1[1]) : (c0[0] + c1[0]);
            float sb = odd ? (c0[3] + c1[3]) : (c0[2] + c1[2]);
            uint32_t pr = pack_bf16(sa, sb);
            pr = pack_bf16(bf_lo(pr) * SCALE, bf_hi(pr) * SCALE);
            sa = valid ? bf_lo(pr) : NEG_INF;
            sb = valid ? bf_hi(pr) : NEG_INF;
            const float tmax = fmaxf(sa, sb);
            if (__any_sync(0xffffffffu, tmax > m)) {
                float nm = tmax;
#pragma unroll
                for (int o = 16; o > 0; o >>= 1) nm = fmaxf(nm, __shfl_xor_sync(0xffffffffu, nm, o));
                nm = fmaxf(nm, m);
                const float alpha = ex2((m - nm) * LOG2E);
#pragma unroll
                for (int s = 0; s < 8; s++) { acc[s][0] *= alpha; acc[s][1] *= alpha; acc[s][2] *= alpha; acc[s][3] *= alpha; }
                l *= alpha;
                m = nm; msub = nm;
            }
            const float pa = ex2((sa - msub) * LOG2E), pb = ex2((sb - msub) * LOG2E);
            l += pa + pb;
            const uint32_t pp = pack_bf16(pa, pb);
            const uint32_t b0 = __byte_perm(pp, 0, sel0), b1 = __byte_perm(pp, 0, sel1);

            if (st == NSTAGE - 1) cw = combine_stats(m, l, ml, warp, lane);

            const uint32_t vb = sbase + slot * SLOT_BYTES;
            mbar_wait(bar_full + 8 * slot, ph);
#pragma unroll
            for (int s = 0; s < 8; s++) ldsm4t(a[s], vb + coff[s & 3] + (s >> 2) * 128);
#pragma unroll
            for (int s = 0; s < 8; s++) mma16816(acc[s], a[s][0], a[s][1], a[s][2], a[s][3], b0, b1);
            __syncwarp();
            if (lane == 0) mbar_arrive(bar_empty + 8 * slot);
            if (++slot == NSLOT) { slot = 0; ph ^= 1; }

        }
        publish_partial(acc, cw, ob, warp, g, t);
        named_arrive(4, 384);

        {
            const uint4* src = oxp + ((b * 32 + h) * NH + warp * 8 + (lane >> 2)) * 4 + (lane & 3);
            const uint32_t tg = tag & 3;
            uint4 w = ld_relaxed_v4(src);
            const int col = ((lane >> 1) & 7) + 8 * (lane & 1);
            float gate_v = 0.f, x_v = 0.f;
            if (warp == 0) {
                named_sync(5, 64);
                const float* gate = reinterpret_cast<const float*>(smem + OFF_GATE);
                gate_v = gate[col];
                x_v = gate[16 + col];
            }
            for (uint32_t spins = 0;; spins++) {
                const bool ok = (((w.x ^ tg) | (w.y ^ tg) | (w.z ^ tg) | (w.w ^ tg)) & 3u) == 0;
                if (__all_sync(0xffffffffu, ok)) break;
                if (!ok) w = ld_relaxed_v4(src);
                if (spins > SPIN_LIMIT_ITERS) __trap();
            }
            float v0 = __uint_as_float(w.x & ~3u), v1 = __uint_as_float(w.y & ~3u);
            float v2 = __uint_as_float(w.z & ~3u), v3 = __uint_as_float(w.w & ~3u);
            const bool u16 = lane & 16, u8 = lane & 8;
            float a0 = (u16 ? v2 : v0) + __shfl_xor_sync(0xffffffffu, u16 ? v0 : v2, 16);
            float a1 = (u16 ? v3 : v1) + __shfl_xor_sync(0xffffffffu, u16 ? v1 : v3, 16);
            float a = (u8 ? a1 : a0) + __shfl_xor_sync(0xffffffffu, u8 ? a0 : a1, 8);
            a += __shfl_xor_sync(0xffffffffu, a, 4);
            float* fin = reinterpret_cast<float*>(smem + OFF_FIN);
            if (!(lane & 4)) fin[warp * 16 + 4 * (lane & 3) + (u16 ? 2 : 0) + (u8 ? 1 : 0)] = a;
            if (warp != 0) {
                __syncwarp();
                named_arrive(6, 128);
            } else {
                named_sync(6, 128);
                if (lane < 16) {
                    const float sum = (fin[lane] + fin[16 + lane]) + (fin[32 + lane] + fin[48 + lane]);
                    out[b * DM + h * 16 + col] = __float2bfloat16_rn(x_v + bf16r(bf16r(sum) * gate_v));
                }
            }
        }
        return;
    }

    const int hw = warp - 4;
    cluster_arrive_relaxed();
    const uint32_t tag = ld_epoch(late(epoch_) + blockIdx.x) + 1;
    cluster_wait();
    if (hw < 4) {
        const uint32_t abase = sbase + OFF_WQ + (uint32_t)((mi >> 1) * 8 + r) * 128 + (uint32_t)(((2 * hw + (mi & 1)) ^ r) << 4);
        const uint4* xs = reinterpret_cast<const uint4*>(smem + OFF_XS + ((g & 1) * 4 + t) * (68 * 4));
        float qa[4][4];
#pragma unroll
        for (int i = 0; i < 4; i++) { qa[i][0] = 0.f; qa[i][1] = 0.f; qa[i][2] = 0.f; qa[i][3] = 0.f; }
        named_sync(1, 192);
#pragma unroll
        for (int half = 0; half < 2; half++) {
            uint32_t xw[32];
#pragma unroll
            for (int i = 0; i < 8; i++) {
                const uint4 v = xs[half * 8 + i];
                xw[4 * i] = v.x; xw[4 * i + 1] = v.y; xw[4 * i + 2] = v.z; xw[4 * i + 3] = v.w;
            }
            mbar_wait(bar_wq + 8 * half, 0);
#pragma unroll
            for (int ks = 0; ks < 16; ks++) {
                uint32_t a[4];
                ldsm4t(a, abase + (half * 16 + ks) * 2048);
                mma16816(qa[ks & 3], a[0], a[1], a[2], a[3], xw[2 * ks], xw[2 * ks + 1]);
            }
        }
        const int ci = t;
        float v = 0.f;
#pragma unroll
        for (int i = 0; i < 4; i++) v = (ci == i) ? ((qa[0][i] + qa[1][i]) + (qa[2][i] + qa[3][i])) : v;
        const float vo = __shfl_xor_sync(0xffffffffu, v, 4);
        if (!(g & 1)) {
            const uint32_t dst = t & 1;
            const uint32_t word = (uint32_t)(rank * 32 + hw * 8 + (t >> 1) * 4 + (g >> 1));
            st_async_u32(mapa(sbase + OFF_QBF + word * 4, dst), pack_bf16(v, vo), mapa(bar_q, dst));
        }
        asm volatile("fence.proxy.async.shared::cta;" ::: "memory");
        __syncwarp();
        if (lane == 0) mbar_arrive(bar_scr);
    }
    if (hw == 0) {
        const int gg = lane & 7, f = lane >> 3;
        const Word2 w = poll_word2(fxp + ((f * NB + b) * 32 + h) * 8 + gg, tag, 500);
        float s0 = __uint_as_float((uint32_t)w.a), s1 = __uint_as_float((uint32_t)w.b);
        s0 += __shfl_xor_sync(0xffffffffu, s0, 8);  s1 += __shfl_xor_sync(0xffffffffu, s1, 8);
        s0 += __shfl_xor_sync(0xffffffffu, s0, 16); s1 += __shfl_xor_sync(0xffffffffu, s1, 16);
        if (lane < 8) {
            float* gate = reinterpret_cast<float*>(smem + OFF_GATE);
            gate[gg] = bf16r(silu_f(bf16r(s0)));
            gate[gg + 8] = bf16r(silu_f(bf16r(s1)));
            gate[16 + gg] = __bfloat162float(x[b * DM + h * 16 + gg]);
            gate[24 + gg] = __bfloat162float(x[b * DM + h * 16 + gg + 8]);
        }
        __syncwarp();
        named_arrive(5, 64);
    }

    {
        const uint32_t base = sbase + OFF_WO + hw * 2048 + (uint32_t)((mi >> 1) * 8 + r) * 128;
        const uint32_t xo = (uint32_t)((mi & 1) ^ r) << 4;
        const uint4* obp = reinterpret_cast<const uint4*>(ob + (g & 3) * 80 + t * 20);
        const int sdst = (t & 1) * 2 + (t >> 1);
        uint2* dst = reinterpret_cast<uint2*>(oxp + ((b * 32 + 4 * hw + sdst) * NH + h) * 4) + g;
        mbar_wait(bar_wo, 0);
        {
            uint32_t wf[7][4][4];
#pragma unroll
            for (int kk = 0; kk < 7; kk++)
#pragma unroll
                for (int s = 0; s < 4; s++) ldsm4t(wf[kk][s], base + kk * WO_PIECE_BYTES + (xo ^ (s << 5)));
            st_relaxed_v2(dst, (tag - 1) & 3, (tag - 1) & 3);
            named_sync(4, 384);
            float pacc[4][4];
#pragma unroll
            for (int s = 0; s < 4; s++) { pacc[s][0] = 0.f; pacc[s][1] = 0.f; pacc[s][2] = 0.f; pacc[s][3] = 0.f; }
            uint4 ow = obp[0];
#pragma unroll
            for (int s = 0; s < 4; s++) mma16816(pacc[s], wf[0][s][0], wf[0][s][1], wf[0][s][2], wf[0][s][3], ow.x, ow.y);
#pragma unroll
            for (int s = 0; s < 4; s++) mma16816(pacc[s], wf[1][s][0], wf[1][s][1], wf[1][s][2], wf[1][s][3], ow.z, ow.w);
#pragma unroll
            for (int i = 1; i < 3; i++) {
                ow = obp[i];
#pragma unroll
                for (int s = 0; s < 4; s++)
                    mma16816(pacc[s], wf[2 * i][s][0], wf[2 * i][s][1], wf[2 * i][s][2], wf[2 * i][s][3], ow.x, ow.y);
#pragma unroll
                for (int s = 0; s < 4; s++)
                    mma16816(pacc[s], wf[2 * i + 1][s][0], wf[2 * i + 1][s][1], wf[2 * i + 1][s][2], wf[2 * i + 1][s][3], ow.z, ow.w);
            }
            ow = obp[3];
#pragma unroll
            for (int s = 0; s < 4; s++) mma16816(pacc[s], wf[6][s][0], wf[6][s][1], wf[6][s][2], wf[6][s][3], ow.x, ow.y);
#pragma unroll
            for (int s = 0; s < 4; s++) {
                uint32_t w7[4];
                ldsm4t(w7, base + 7 * WO_PIECE_BYTES + (xo ^ (s << 5)));
                mma16816(pacc[s], w7[0], w7[1], w7[2], w7[3], ow.z, ow.w);
            }
            float v0[4], v1[4];
#pragma unroll
            for (int s = 0; s < 4; s++) { v0[s] = pacc[s][0] + pacc[s][1]; v1[s] = pacc[s][2] + pacc[s][3]; }
            const bool to = t & 1, th = t >> 1;
            const float ka0 = to ? v0[2] : v0[0], ka1 = to ? v0[3] : v0[1], kb0 = to ? v1[2] : v1[0], kb1 = to ? v1[3] : v1[1];
            const float sa0 = to ? v0[0] : v0[2], sa1 = to ? v0[1] : v0[3], sb0 = to ? v1[0] : v1[2], sb1 = to ? v1[1] : v1[3];
            const float sa = th ? sa1 : sa0, sb = th ? sb1 : sb0;
            const float ra = __shfl_xor_sync(0xffffffffu, sa, 1), rb = __shfl_xor_sync(0xffffffffu, sb, 1);
            const float o0 = (th ? ka1 : ka0) + ra, o1 = (th ? kb1 : kb0) + rb;
            const uint32_t tg = tag & 3;
            st_relaxed_v2(dst, (__float_as_uint(o0) & ~3u) | tg, (__float_as_uint(o1) & ~3u) | tg);
        }
    }
}

}

extern "C" void kernel_launch(void* const* d_in, const int* in_sizes, int n_in, void* d_out, int out_size) {
    (void)in_sizes; (void)n_in; (void)out_size;
    const __nv_bfloat16* x = (const __nv_bfloat16*)d_in[0];
    const __nv_bfloat16* kc = (const __nv_bfloat16*)d_in[1];
    const __nv_bfloat16* vc = (const __nv_bfloat16*)d_in[2];
    const __nv_bfloat16* wq = (const __nv_bfloat16*)d_in[3];
    const __nv_bfloat16* wo = (const __nv_bfloat16*)d_in[4];
    const __nv_bfloat16* w1 = (const __nv_bfloat16*)d_in[6];
    const __nv_bfloat16* w2 = (const __nv_bfloat16*)d_in[7];
    typedef CUresult (*EncodeFn)(CUtensorMap*, CUtensorMapDataType, cuuint32_t, void*, const cuuint64_t*, const cuuint64_t*,
                                 const cuuint32_t*, const cuuint32_t*, CUtensorMapInterleave, CUtensorMapSwizzle,
                                 CUtensorMapL2promotion, CUtensorMapFloatOOBfill);
    static unsigned int *epoch = nullptr, *progp = nullptr;
    static uint4* oxp = nullptr;
    static Word2* fxp = nullptr;
    static EncodeFn encode = nullptr;
    if (!epoch) {
        cudaFuncSetAttribute(fused_decode_kernel, cudaFuncAttributeMaxDynamicSharedMemorySize, SMEM_BYTES);
        void* fn = nullptr;
        cudaDriverEntryPointQueryResult qr;
        cudaGetDriverEntryPoint("cuTensorMapEncodeTiled", &fn, cudaEnableDefault, &qr);
        encode = (EncodeFn)fn;
        cudaGetSymbolAddress((void**)&oxp, g_ox);
        cudaGetSymbolAddress((void**)&fxp, g_fx);
        cudaGetSymbolAddress((void**)&progp, g_prog);
        cudaGetSymbolAddress((void**)&epoch, g_epoch);
    }
    CUtensorMap wq_map, wo_map;
    const cuuint32_t estride[2] = {1, 1};
    {
        const cuuint64_t gdim[2] = {(cuuint64_t)(NH * DH), (cuuint64_t)DM}, gstride[1] = {(cuuint64_t)(NH * DH * 2)};
        const cuuint32_t box[2] = {64, 256};
        encode(&wq_map, CU_TENSOR_MAP_DATA_TYPE_BFLOAT16, 2, (void*)wq, gdim, gstride, box, estride, CU_TENSOR_MAP_INTERLEAVE_NONE,
               CU_TENSOR_MAP_SWIZZLE_128B, CU_TENSOR_MAP_L2_PROMOTION_NONE, CU_TENSOR_MAP_FLOAT_OOB_FILL_NONE);
    }
    {
        const cuuint64_t gdim[3] = {64, (cuuint64_t)(NH * DH), 8}, gstride[2] = {(cuuint64_t)(DM * 2), 128};
        const cuuint32_t box[3] = {64, 16, 8}, es3[3] = {1, 1, 1};
        encode(&wo_map, CU_TENSOR_MAP_DATA_TYPE_BFLOAT16, 3, (void*)wo, gdim, gstride, box, es3, CU_TENSOR_MAP_INTERLEAVE_NONE,
               CU_TENSOR_MAP_SWIZZLE_128B, CU_TENSOR_MAP_L2_PROMOTION_NONE, CU_TENSOR_MAP_FLOAT_OOB_FILL_NONE);
    }
    fused_decode_kernel<<<NCTA, NTHREADS, SMEM_BYTES, cudaStreamPerThread>>>(x, kc, vc, (__nv_bfloat16*)d_out, w1, w2,
                                                                             epoch, progp, oxp, fxp, wq_map, wo_map);
}
```

```cpp
#include <cuda_runtime.h>
#include <cuda.h>
#include <cuda_bf16.h>
#include <stdint.h>

namespace {

constexpr int NB = 4, DM = 512, NH = 32, SK = 8192, DH = 128, FF = 1376;
constexpr int NATT = NB * NH;
constexpr int NFFN = 4;
constexpr int NCTA = NATT + NFFN;
constexpr int NTHREADS = 416;

constexpr int TILE = 64;
constexpr int SLOT_BYTES = TILE * DH * 2;
constexpr int NSLOT = 6;
constexpr int WIN_BASE = 4, WIN_MIN = 1, WIN_MAX = NSLOT;
constexpr int WIN_P_SHIFT = 8;
constexpr int WIN_I_SHIFT = 4;
constexpr int NSTAGE = SK / TILE;
constexpr int NSEQ = 2 * NSTAGE;
constexpr int RING_BYTES = NSLOT * SLOT_BYTES;
constexpr int WO_BYTES = DH * DM * 2;
constexpr int WO_PIECES = 8;
constexpr int WO_PIECE_BYTES = WO_BYTES / WO_PIECES;

constexpr int OFF_WO = RING_BYTES;
constexpr int OFF_WQ = OFF_WO;
constexpr int WQ_BYTES = DM * 128;
constexpr int OFF_XS = OFF_WO + WQ_BYTES;
constexpr int OFF_MISC = OFF_WO + WO_BYTES;
constexpr int OFF_OB = OFF_MISC;
constexpr int OFF_ML = OFF_OB + 1280;
constexpr int OFF_QBF = OFF_ML + 32;
constexpr int OFF_GATE = OFF_QBF + 256;
constexpr int OFF_FIN = OFF_GATE + 128;
constexpr int OFF_BAR = OFF_FIN + 256;
constexpr int SMEM_BYTES = OFF_BAR + 160;
static_assert(SMEM_BYTES <= 232448, "smem");

constexpr int FSL = FF / NFFN;
constexpr int FOFF_XN = 0;
constexpr int FOFF_HP = 8192;
constexpr int FOFF_HS = FOFF_HP + 8 * 4 * FSL * 4;
constexpr int FOFF_OP = FOFF_HS + FSL * 16;

struct __align__(16) Word2 { unsigned long long a, b; };

__device__ unsigned int g_epoch[NCTA];
__device__ unsigned int g_prog[2];
__device__ uint4 g_ox[NB][32][NH][4];
__device__ Word2 g_fx[NFFN][NB][32][8];


__device__ __forceinline__ uint32_t smem_u32(const void* p) { return (uint32_t)__cvta_generic_to_shared(p); }

__device__ __forceinline__ void mbar_init(uint32_t bar, uint32_t count) {
    asm volatile("mbarrier.init.shared::cta.b64 [%0], %1;" ::"r"(bar), "r"(count) : "memory");
}
__device__ __forceinline__ void mbar_expect_tx(uint32_t bar, uint32_t bytes) {
    asm volatile("mbarrier.arrive.expect_tx.shared::cta.b64 _, [%0], %1;" ::"r"(bar), "r"(bytes) : "memory");
}
__device__ __forceinline__ void mbar_arrive(uint32_t bar) {
    asm volatile("mbarrier.arrive.shared::cta.b64 _, [%0];" ::"r"(bar) : "memory");
}
__device__ __forceinline__ bool mbar_try(uint32_t bar, uint32_t parity) {
    uint32_t ok;
    asm volatile("{\n.reg .pred p;\nmbarrier.try_wait.parity.shared::cta.b64 p, [%1], %2;\nselp.u32 %0, 1, 0, p;\n}"
                 : "=r"(ok) : "r"(bar), "r"(parity) : "memory");
    return ok != 0;
}
constexpr long long SPIN_LIMIT_CLK = 4000000000LL;
constexpr uint32_t SPIN_LIMIT_ITERS = 1u << 23;
__device__ __forceinline__ void mbar_wait(uint32_t bar, uint32_t parity) {
    if (mbar_try(bar, parity)) return;
    long long t0 = clock64();
    while (!mbar_try(bar, parity)) {
        if (clock64() - t0 > SPIN_LIMIT_CLK) __trap();
    }
}
__device__ __forceinline__ void bulk_load(uint32_t dst, const void* src, uint32_t bytes, uint32_t bar, uint64_t pol) {
    asm volatile("cp.async.bulk.shared::cluster.global.mbarrier::complete_tx::bytes.L2::cache_hint [%0], [%1], %2, [%3], %4;"
                 ::"r"(dst), "l"(src), "r"(bytes), "r"(bar), "l"(pol) : "memory");
}
__device__ __forceinline__ void tensor_load_2d(uint32_t dst, const CUtensorMap* tm, int c0, int c1, uint32_t bar) {
    asm volatile("cp.async.bulk.tensor.2d.shared::cluster.global.mbarrier::complete_tx::bytes [%0], [%1, {%3, %4}], [%2];"
                 ::"r"(dst), "l"(tm), "r"(bar), "r"(c0), "r"(c1) : "memory");
}
__device__ __forceinline__ void tensor_load_3d(uint32_t dst, const CUtensorMap* tm, int c0, int c1, int c2, uint32_t bar) {
    asm volatile("cp.async.bulk.tensor.3d.shared::cluster.global.mbarrier::complete_tx::bytes [%0], [%1, {%3, %4, %5}], [%2];"
                 ::"r"(dst), "l"(tm), "r"(bar), "r"(c0), "r"(c1), "r"(c2) : "memory");
}
__device__ __forceinline__ void named_sync(int id, int n) { asm volatile("bar.sync %0, %1;" ::"r"(id), "r"(n) : "memory"); }
__device__ __forceinline__ void named_arrive(int id, int n) { asm volatile("bar.arrive %0, %1;" ::"r"(id), "r"(n) : "memory"); }

__device__ __forceinline__ void cluster_arrive_relaxed() { asm volatile("barrier.cluster.arrive.relaxed.aligned;" ::: "memory"); }
__device__ __forceinline__ void cluster_wait() { asm volatile("barrier.cluster.wait.aligned;" ::: "memory"); }
__device__ __forceinline__ uint32_t mapa(uint32_t addr, uint32_t rank) {
    uint32_t r;
    asm("mapa.shared::cluster.u32 %0, %1, %2;" : "=r"(r) : "r"(addr), "r"(rank));
    return r;
}
__device__ __forceinline__ void st_async_u32(uint32_t addr, uint32_t v, uint32_t bar) {
    asm volatile("st.async.weak.shared::cluster.mbarrier::complete_tx::bytes.u32 [%0], %1, [%2];" ::"r"(addr), "r"(v), "r"(bar) : "memory");
}

__device__ __forceinline__ void ldsm4(uint32_t (&r)[4], uint32_t addr) {
    asm volatile("ldmatrix.sync.aligned.m8n8.x4.shared.b16 {%0,%1,%2,%3}, [%4];"
                 : "=r"(r[0]), "=r"(r[1]), "=r"(r[2]), "=r"(r[3]) : "r"(addr) : "memory");
}
__device__ __forceinline__ void ldsm4t(uint32_t (&r)[4], uint32_t addr) {
    asm volatile("ldmatrix.sync.aligned.m8n8.x4.trans.shared.b16 {%0,%1,%2,%3}, [%4];"
                 : "=r"(r[0]), "=r"(r[1]), "=r"(r[2]), "=r"(r[3]) : "r"(addr) : "memory");
}
__device__ __forceinline__ void mma16816(float (&c)[4], uint32_t a0, uint32_t a1, uint32_t a2, uint32_t a3, uint32_t b0, uint32_t b1) {
    asm volatile("mma.sync.aligned.m16n8k16.row.col.f32.bf16.bf16.f32 {%0,%1,%2,%3}, {%4,%5,%6,%7}, {%8,%9}, {%0,%1,%2,%3};"
                 : "+f"(c[0]), "+f"(c[1]), "+f"(c[2]), "+f"(c[3])
                 : "r"(a0), "r"(a1), "r"(a2), "r"(a3), "r"(b0), "r"(b1));
}
__device__ __forceinline__ uint32_t pack_bf16(float lo, float hi) {
    uint32_t r;
    asm("cvt.rn.bf16x2.f32 %0, %1, %2;" : "=r"(r) : "f"(hi), "f"(lo));
    return r;
}
__device__ __forceinline__ float bf_lo(uint32_t u) { return __uint_as_float(u << 16); }
__device__ __forceinline__ float bf_hi(uint32_t u) { return __uint_as_float(u & 0xffff0000u); }
__device__ __forceinline__ float bf16r(float x) { return __bfloat162float(__float2bfloat16_rn(x)); }
__device__ __forceinline__ float ex2(float x) {
    float y;
    asm("ex2.approx.ftz.f32 %0, %1;" : "=f"(y) : "f"(x));
    return y;
}
__device__ __forceinline__ float silu_f(float x) { return x / (1.0f + expf(-x)); }

__device__ __forceinline__ uint4 ldg_nc(const void* p) {
    uint4 v;
    asm volatile("ld.global.nc.L1::no_allocate.v4.u32 {%0,%1,%2,%3}, [%4];" : "=r"(v.x), "=r"(v.y), "=r"(v.z), "=r"(v.w) : "l"(p));
    return v;
}
__device__ __forceinline__ Word2 ld_word2(const Word2* p) {
    Word2 v;
    asm volatile("ld.relaxed.gpu.global.v2.b64 {%0,%1}, [%2];" : "=l"(v.a), "=l"(v.b) : "l"(p) : "memory");
    return v;
}
__device__ __forceinline__ void st_word2(Word2* p, unsigned long long a, unsigned long long b) {
    asm volatile("st.relaxed.gpu.global.v2.b64 [%0], {%1,%2};" ::"l"(p), "l"(a), "l"(b) : "memory");
}
__device__ __forceinline__ uint4 ld_relaxed_v4(const uint4* p) {
    uint4 v;
    asm volatile("ld.relaxed.gpu.global.v4.u32 {%0,%1,%2,%3}, [%4];" : "=r"(v.x), "=r"(v.y), "=r"(v.z), "=r"(v.w) : "l"(p) : "memory");
    return v;
}
__device__ __forceinline__ void st_relaxed_v2(uint2* p, uint32_t a, uint32_t b) {
    asm volatile("st.relaxed.gpu.global.v2.u32 [%0], {%1,%2};" ::"l"(p), "r"(a), "r"(b) : "memory");
}
template <typename T>
__device__ __forceinline__ T* late(T* p) { asm volatile("" : "+l"(p) :: "memory"); return p; }
__device__ __forceinline__ uint32_t ld_epoch(const unsigned int* p) {
    uint32_t v;
    asm volatile("ld.relaxed.gpu.global.u32 %0, [%1];" : "=r"(v) : "l"(p) : "memory");
    return v;
}
__device__ __forceinline__ unsigned long long mkword(uint32_t payload, uint32_t tag) {
    return ((unsigned long long)tag << 32) | payload;
}
__device__ __forceinline__ bool word2_ok(const Word2& w, uint32_t tag) {
    return (uint32_t)(w.a >> 32) == tag && (uint32_t)(w.b >> 32) == tag;
}
__device__ __forceinline__ Word2 poll_word2(const Word2* p, uint32_t tag, unsigned sleep_ns) {
    Word2 w = ld_word2(p);
    if (__all_sync(0xffffffffu, word2_ok(w, tag))) return w;
    long long t0 = clock64();
    while (true) {
        if (sleep_ns) __nanosleep(sleep_ns);
        w = ld_word2(p);
        if (__all_sync(0xffffffffu, word2_ok(w, tag))) return w;
        if (clock64() - t0 > SPIN_LIMIT_CLK) __trap();
    }
}

__device__ __forceinline__ void layernorm_row(const uint4 a, const uint4 b, float (&v)[16]) {
    v[0] = bf_lo(a.x); v[1] = bf_hi(a.x); v[2] = bf_lo(a.y); v[3] = bf_hi(a.y);
    v[4] = bf_lo(a.z); v[5] = bf_hi(a.z); v[6] = bf_lo(a.w); v[7] = bf_hi(a.w);
    v[8] = bf_lo(b.x); v[9] = bf_hi(b.x); v[10] = bf_lo(b.y); v[11] = bf_hi(b.y);
    v[12] = bf_lo(b.z); v[13] = bf_hi(b.z); v[14] = bf_lo(b.w); v[15] = bf_hi(b.w);
    float s = 0.f;
#pragma unroll
    for (int i = 0; i < 16; i++) s += v[i];
#pragma unroll
    for (int o = 16; o > 0; o >>= 1) s += __shfl_xor_sync(0xffffffffu, s, o);
    const float mean = s * (1.0f / DM);
    float q = 0.f;
#pragma unroll
    for (int i = 0; i < 16; i++) { float d = v[i] - mean; q += d * d; }
#pragma unroll
    for (int o = 16; o > 0; o >>= 1) q += __shfl_xor_sync(0xffffffffu, q, o);
    const float mb = bf16r(mean);
    const float vb = bf16r(q * (1.0f / DM));
    const float den = bf16r(sqrtf(bf16r(vb + 1e-5f)));
#pragma unroll
    for (int i = 0; i < 16; i++) v[i] = bf16r(bf16r(v[i] - mb) / den);
}

__device__ __forceinline__ void ffn_gemv(float (&acc)[4][8], const __nv_bfloat16* __restrict__ wp, int ld,
                                         const float4* act, int r0, int r1) {
    for (int r = r0; r < r1; r += 16) {
        uint4 w[16];
#pragma unroll
        for (int u = 0; u < 16; u++) w[u] = (r + u < r1) ? ldg_nc(wp + (size_t)(r + u) * ld) : make_uint4(0, 0, 0, 0);
#pragma unroll
        for (int u = 0; u < 16; u++) {
            const float4 xv = act[min(r + u, r1 - 1)];
            const float wf[8] = {bf_lo(w[u].x), bf_hi(w[u].x), bf_lo(w[u].y), bf_hi(w[u].y),
                                 bf_lo(w[u].z), bf_hi(w[u].z), bf_lo(w[u].w), bf_hi(w[u].w)};
#pragma unroll
            for (int e = 0; e < 8; e++) {
                acc[0][e] = fmaf(xv.x, wf[e], acc[0][e]); acc[1][e] = fmaf(xv.y, wf[e], acc[1][e]);
                acc[2][e] = fmaf(xv.z, wf[e], acc[2][e]); acc[3][e] = fmaf(xv.w, wf[e], acc[3][e]);
            }
        }
    }
}

__device__ __forceinline__ void ffn_cta(unsigned char* smem, int f, const __nv_bfloat16* __restrict__ x,
                                        const __nv_bfloat16* __restrict__ w1, const __nv_bfloat16* __restrict__ w2,
                                        unsigned int* epoch, Word2* fxp) {
    const int tid = threadIdx.x, warp = tid >> 5, lane = tid & 31;
    float* xn4 = reinterpret_cast<float*>(smem + FOFF_XN);
    float* hp = reinterpret_cast<float*>(smem + FOFF_HP);
    float4* hs = reinterpret_cast<float4*>(smem + FOFF_HS);
    float* op = reinterpret_cast<float*>(smem + FOFF_OP);

    const uint32_t tag = ld_epoch(epoch + blockIdx.x) + 1;
    if (warp < 4) {
        const uint4* xr = reinterpret_cast<const uint4*>(x + warp * DM);
        float v[16];
        layernorm_row(ldg_nc(xr + lane), ldg_nc(xr + 32 + lane), v);
#pragma unroll
        for (int i = 0; i < 16; i++) xn4[((i < 8) ? (lane * 8 + i) : (248 + lane * 8 + i)) * 4 + warp] = v[i];
    }
    __syncthreads();
    if (tid == 0) epoch[blockIdx.x] = tag;

    float acc[4][8];
    if (tid < 344) {
        const int cg = tid % 43, ks = tid / 43;
#pragma unroll
        for (int b = 0; b < 4; b++)
#pragma unroll
            for (int e = 0; e < 8; e++) acc[b][e] = 0.f;
        ffn_gemv(acc, w1 + f * FSL + cg * 8, FF, reinterpret_cast<const float4*>(xn4), ks * 64, ks * 64 + 64);
#pragma unroll
        for (int b = 0; b < 4; b++)
#pragma unroll
            for (int e = 0; e < 8; e++) hp[(ks * 4 + b) * FSL + cg * 8 + e] = acc[b][e];
    }
    __syncthreads();
    for (int i = tid; i < 4 * FSL; i += NTHREADS) {
        const int b = i / FSL, c = i % FSL;
        float s = 0.f;
#pragma unroll
        for (int ks = 0; ks < 8; ks++) s += hp[(ks * 4 + b) * FSL + c];
        reinterpret_cast<float*>(hs)[c * 4 + b] = bf16r(silu_f(bf16r(s)));
    }
    __syncthreads();
    if (tid < 384) {
        const int cg = tid & 63, ks = tid >> 6;
#pragma unroll
        for (int b = 0; b < 4; b++)
#pragma unroll
            for (int e = 0; e < 8; e++) acc[b][e] = 0.f;
        ffn_gemv(acc, w2 + (size_t)(f * FSL) * DM + cg * 8, DM, hs, ks * 58, min(ks * 58 + 58, FSL));
#pragma unroll
        for (int b = 0; b < 4; b++)
#pragma unroll
            for (int e = 0; e < 8; e++) op[(ks * 4 + b) * DM + cg * 8 + e] = acc[b][e];
    }
    __syncthreads();
    for (int i = tid; i < NB * 32 * 8; i += NTHREADS) {
        const int b = i >> 8, hh = (i >> 3) & 31, g = i & 7;
        const int c0 = hh * 16 + g;
        float s0 = 0.f, s1 = 0.f;
#pragma unroll
        for (int ks = 0; ks < 6; ks++) { s0 += op[(ks * 4 + b) * DM + c0]; s1 += op[(ks * 4 + b) * DM + c0 + 8]; }
        st_word2(fxp + ((f * NB + b) * 32 + hh) * 8 + g, mkword(__float_as_uint(s0), tag), mkword(__float_as_uint(s1), tag));
    }
}

template <int NT>
__device__ __forceinline__ void diag_reduce(const float (&acc)[NT][4], float (&u)[2 * NT]) {
#pragma unroll
    for (int s = 0; s < NT; s++) {
        u[2 * s] = acc[s][0] + acc[s][3];
        u[2 * s + 1] = acc[s][2] + acc[s][1];
    }
#pragma unroll
    for (int L = 0; L < 2 * NT; L++)
        if (!(L & 2)) u[L] += __shfl_xor_sync(0xffffffffu, u[L ^ 2], 1);
#pragma unroll
    for (int L = 0; L < 2 * NT; L++)
        if (!(L & 6)) u[L] += __shfl_xor_sync(0xffffffffu, u[L ^ 4], 2);
}

__device__ __forceinline__ float combine_stats(float m, float l, float* ml, int warp, int lane) {
    const float LOG2E = 1.4426950408889634f;
#pragma unroll
    for (int o = 16; o > 0; o >>= 1) l += __shfl_xor_sync(0xffffffffu, l, o);
    if (lane == 0) *reinterpret_cast<float2*>(ml + warp * 2) = make_float2(m, l);
    named_sync(3, 128);
    const float4 ml01 = *reinterpret_cast<const float4*>(ml), ml23 = *reinterpret_cast<const float4*>(ml + 4);
    const float M = fmaxf(fmaxf(ml01.x, ml01.z), fmaxf(ml23.x, ml23.z));
    const float L = ex2((ml01.x - M) * LOG2E) * ml01.y + ex2((ml01.z - M) * LOG2E) * ml01.w +
                    ex2((ml23.x - M) * LOG2E) * ml23.y + ex2((ml23.z - M) * LOG2E) * ml23.w;
    return ex2((m - M) * LOG2E) / L;
}

__device__ __forceinline__ void publish_partial(const float (&acc)[8][4], float cw, uint32_t* ob, int warp, int g, int t) {
    float u[16];
    diag_reduce<8>(acc, u);
    const bool og = g & 1;
    const float k0 = (og ? u[8] : u[0]) * cw, k1 = (og ? u[9] : u[1]) * cw;
    const float s0 = (og ? u[0] : u[8]) * cw, s1 = (og ? u[1] : u[9]) * cw;
    const float r0 = __shfl_xor_sync(0xffffffffu, s0, 4), r1 = __shfl_xor_sync(0xffffffffu, s1, 4);
    const uint32_t w0 = og ? pack_bf16(r0, k0) : pack_bf16(k0, r0);
    const uint32_t w1 = og ? pack_bf16(r1, k1) : pack_bf16(k1, r1);
    *reinterpret_cast<uint2*>(ob + warp * 80 + (g >> 1) * 20 + (og ? 8 : 0) + 2 * t) = make_uint2(w0, w1);
    __syncwarp();
}

__global__ void __cluster_dims__(2, 1, 1) __launch_bounds__(NTHREADS, 1)
fused_decode_kernel(const __nv_bfloat16* __restrict__ x, const __nv_bfloat16* __restrict__ kc,
                    const __nv_bfloat16* __restrict__ vc, __nv_bfloat16* __restrict__ out,
                    const __nv_bfloat16* __restrict__ w1, const __nv_bfloat16* __restrict__ w2,
                    unsigned int* __restrict__ epoch_, unsigned int* __restrict__ progp,
                    uint4* __restrict__ oxp, Word2* __restrict__ fxp,
                    const __grid_constant__ CUtensorMap wq_map, const __grid_constant__ CUtensorMap wo_map) {
    extern __shared__ __align__(1024) unsigned char smem[];
    const int tid = threadIdx.x, warp = tid >> 5, lane = tid & 31;

    if (blockIdx.x >= NATT) {
        ffn_cta(smem, blockIdx.x - NATT, x, w1, w2, epoch_, fxp);
        return;
    }

    const int a_idx = blockIdx.x;
    const int rank = a_idx & 1, h = (a_idx >> 1) & 31, bp = a_idx >> 6;
    const int b = 2 * bp + rank, bh = b * NH + h;
    const uint32_t sbase = smem_u32(smem);
    const uint32_t bar_full = sbase + OFF_BAR;
    const uint32_t bar_empty = bar_full + 8 * NSLOT;
    const uint32_t bar_wo = bar_empty + 8 * NSLOT;
    const uint32_t bar_q = bar_wo + 8;
    const uint32_t bar_scr = bar_q + 8;
    const uint32_t bar_wq = bar_scr + 8;

    if (warp == 12) {
        const char* kp = reinterpret_cast<const char*>(kc) + (size_t)bh * SK * DH * 2;
        const char* vp = reinterpret_cast<const char*>(vc) + (size_t)bh * SK * DH * 2;
        uint64_t pol;
        asm volatile("createpolicy.fractional.L2::evict_first.b64 %0, 1.0;" : "=l"(pol));
        if (lane == 0) {
            mbar_init(bar_wq, 1);
            mbar_init(bar_wq + 8, 1);
#pragma unroll
            for (int i = 0; i < 2; i++) {
                mbar_expect_tx(bar_wq + 8 * i, WQ_BYTES / 2);
                tensor_load_2d(sbase + OFF_WQ + i * (WQ_BYTES / 2), &wq_map, h * DH + rank * 64, i * 256, bar_wq + 8 * i);
            }
            for (int s = 0; s < NSLOT; s++) mbar_init(bar_full + 8 * s, 1);
            for (int s = 0; s < WIN_BASE; s++) {
                mbar_expect_tx(bar_full + 8 * s, SLOT_BYTES);
                bulk_load(sbase + s * SLOT_BYTES, ((s & 1) ? vp : kp) + (size_t)(s >> 1) * SLOT_BYTES, SLOT_BYTES, bar_full + 8 * s, pol);
            }
            for (int s = 0; s < NSLOT; s++) mbar_init(bar_empty + 8 * s, 4);
            mbar_init(bar_wo, 1);
            mbar_init(bar_q, 1);
            mbar_init(bar_scr, 4);
            mbar_expect_tx(bar_q, 256);
            asm volatile("fence.mbarrier_init.release.cluster;" ::: "memory");
            asm volatile("prefetch.tensormap [%0];" ::"l"(&wo_map) : "memory");
        }
        __syncwarp();
        cluster_arrive_relaxed();
        unsigned int* epoch = late(epoch_);
        const uint32_t tag = ld_epoch(epoch + blockIdx.x) + 1;
        cluster_wait();
        if (lane == 0) {
            unsigned int* prog = progp + (tag & 1);
            if (blockIdx.x == 0) progp[(tag + 1) & 1] = 0;
            int win = WIN_BASE, integ = 0, nupd = 0;
            uint32_t pend = 0;
            int slot = WIN_BASE % NSLOT;
            int released = -1, rslot = 0;
            uint32_t rph = 0;
            for (int seq = WIN_BASE; seq < NSEQ; seq++) {
                if (!(seq & 1)) {
                    if (nupd > 0) {
                        int ctl = (int)(2 * pend) - 2 * (nupd - 1) * NATT - 128;
                        integ = min(max(integ + ctl, -(3 << (WIN_P_SHIFT + WIN_I_SHIFT))), 3 << (WIN_P_SHIFT + WIN_I_SHIFT));
                        ctl += (integ >> WIN_I_SHIFT) + 32 + 64 * (nupd & 3);
                        win = min(max(WIN_BASE + (ctl >> WIN_P_SHIFT), WIN_MIN), WIN_MAX);
                    }
                    pend = atomicAdd(prog, 1u);
                    nupd++;
                }
                while (released < seq - win) {
                    released++;
                    mbar_wait(bar_empty + 8 * rslot, rph);
                    if (++rslot == NSLOT) { rslot = 0; rph ^= 1; }
                }
                mbar_expect_tx(bar_full + 8 * slot, SLOT_BYTES);
                bulk_load(sbase + slot * SLOT_BYTES, ((seq & 1) ? vp : kp) + (size_t)(seq >> 1) * SLOT_BYTES, SLOT_BYTES,
                          bar_full + 8 * slot, pol);
                if (seq >= 8 && seq < 8 + 2 * WO_PIECES && !(seq & 1)) {
                    const int p = (seq - 8) >> 1;
                    if (p == 0) { mbar_wait(bar_scr, 0); mbar_expect_tx(bar_wo, WO_BYTES); }
                    tensor_load_3d(sbase + OFF_WO + p * WO_PIECE_BYTES, &wo_map, 0, h * DH + p * 16, 0, bar_wo);
                }
                if (++slot == NSLOT) slot = 0;
            }
            epoch[blockIdx.x] = tag;
        }
        return;
    }

    const int g = lane >> 2, t = lane & 3;
    const int mi = lane >> 3, r = lane & 7;
    uint32_t* ob = reinterpret_cast<uint32_t*>(smem + OFF_OB);

    if (warp < 4) {
        if (warp < 2) {
            const uint4* xr = reinterpret_cast<const uint4*>(x + (2 * bp + warp) * DM);
            const uint4 xa = ldg_nc(xr + lane), xb = ldg_nc(xr + 32 + lane);
            cluster_arrive_relaxed();
            float v[16];
            layernorm_row(xa, xb, v);
            uint32_t* xs = reinterpret_cast<uint32_t*>(smem + OFF_XS) + warp * (4 * 68);
#pragma unroll
            for (int j = 0; j < 4; j++) {
                xs[j * 68 + lane] = pack_bf16(v[2 * j], v[2 * j + 1]);
                xs[j * 68 + 32 + lane] = pack_bf16(v[8 + 2 * j], v[8 + 2 * j + 1]);
            }
            __syncwarp();
            named_arrive(1, 192);
        } else {
            cluster_arrive_relaxed();
        }
        const uint32_t tag = ld_epoch(late(epoch_) + blockIdx.x) + 1;
        cluster_wait();
        mbar_wait(bar_q, 0);
        const uint32_t* qbf = reinterpret_cast<const uint32_t*>(smem + OFF_QBF);
        uint32_t qf[16];
#pragma unroll
        for (int L = 0; L < 16; L++) qf[L] = qbf[((L & 8) | ((L & 7) ^ g)) * 4 + t];

        const uint32_t rowoff = (uint32_t)(warp * 16 + (mi >> 1) * 8 + r) * 256;
        uint32_t coff[4];
#pragma unroll
        for (int j = 0; j < 4; j++) coff[j] = rowoff + ((((mi & 1) ^ r) ^ (2 * j)) << 4);

        const bool valid = (t == (g >> 1));
        const bool odd = g & 1;
        const uint32_t sel0 = odd ? 0x1044u : 0x4410u, sel1 = odd ? 0x3244u : 0x4432u;
        const float NEG_INF = __int_as_float(0xff800000);
        const float SCALE = 0.08838834764831845f, LOG2E = 1.4426950408889634f;

        float acc[8][4];
#pragma unroll
        for (int s = 0; s < 8; s++) { acc[s][0] = 0.f; acc[s][1] = 0.f; acc[s][2] = 0.f; acc[s][3] = 0.f; }
        float m = NEG_INF, msub = 0.f, l = 0.f, cw = 0.f;
        float* ml = reinterpret_cast<float*>(smem + OFF_ML);
        int slot = 0;
        uint32_t ph = 0;

        for (int st = 0; st < NSTAGE; st++) {
            uint32_t a[8][4];
            const uint32_t kb = sbase + slot * SLOT_BYTES;
            mbar_wait(bar_full + 8 * slot, ph);
#pragma unroll
            for (int s = 0; s < 8; s++) ldsm4(a[s], kb + coff[s & 3] + (s >> 2) * 128);
            float c0[4] = {0.f, 0.f, 0.f, 0.f}, c1[4] = {0.f, 0.f, 0.f, 0.f};
#pragma unroll
            for (int s = 0; s < 8; s += 2) {
                mma16816(c0, a[s][0], a[s][2], a[s][1], a[s][3], qf[2 * s], qf[2 * s + 1]);
                mma16816(c1, a[s + 1][0], a[s + 1][2], a[s + 1][1], a[s + 1][3], qf[2 * s + 2], qf[2 * s + 3]);
            }
            __syncwarp();
            if (lane == 0) mbar_arrive(bar_empty + 8 * slot);
            if (++slot == NSLOT) { slot = 0; ph ^= 1; }

            float sa = odd ? (c0[1] + c1[1]) : (c0[0] + c1[0]);
            float sb = odd ? (c0[3] + c1[3]) : (c0[2] + c1[2]);
            uint32_t pr = pack_bf16(sa, sb);
            pr = pack_bf16(bf_lo(pr) * SCALE, bf_hi(pr) * SCALE);
            sa = valid ? bf_lo(pr) : NEG_INF;
            sb = valid ? bf_hi(pr) : NEG_INF;
            const float tmax = fmaxf(sa, sb);
            if (__any_sync(0xffffffffu, tmax > m)) {
                float nm = tmax;
#pragma unroll
                for (int o = 16; o > 0; o >>= 1) nm = fmaxf(nm, __shfl_xor_sync(0xffffffffu, nm, o));
                nm = fmaxf(nm, m);
                const float alpha = ex2((m - nm) * LOG2E);
#pragma unroll
                for (int s = 0; s < 8; s++) { acc[s][0] *= alpha; acc[s][1] *= alpha; acc[s][2] *= alpha; acc[s][3] *= alpha; }
                l *= alpha;
                m = nm; msub = nm;
            }
            const float pa = ex2((sa - msub) * LOG2E), pb = ex2((sb - msub) * LOG2E);
            l += pa + pb;
            const uint32_t pp = pack_bf16(pa, pb);
            const uint32_t b0 = __byte_perm(pp, 0, sel0), b1 = __byte_perm(pp, 0, sel1);

            if (st == NSTAGE - 1) cw = combine_stats(m, l, ml, warp, lane);

            const uint32_t vb = sbase + slot * SLOT_BYTES;
            mbar_wait(bar_full + 8 * slot, ph);
#pragma unroll
            for (int s = 0; s < 8; s++) ldsm4t(a[s], vb + coff[s & 3] + (s >> 2) * 128);
#pragma unroll
            for (int s = 0; s < 8; s++) mma16816(acc[s], a[s][0], a[s][1], a[s][2], a[s][3], b0, b1);
            __syncwarp();
            if (lane == 0) mbar_arrive(bar_empty + 8 * slot);
            if (++slot == NSLOT) { slot = 0; ph ^= 1; }

        }
        publish_partial(acc, cw, ob, warp, g, t);
        named_arrive(4, 384);

        {
            const uint4* src = oxp + ((b * 32 + h) * NH + warp * 8 + (lane >> 2)) * 4 + (lane & 3);
            const uint32_t tg = tag & 3;
            uint4 w = ld_relaxed_v4(src);
            const int col = ((lane >> 1) & 7) + 8 * (lane & 1);
            float gate_v = 0.f, x_v = 0.f;
            if (warp == 0) {
                named_sync(5, 64);
                const float* gate = reinterpret_cast<const float*>(smem + OFF_GATE);
                gate_v = gate[col];
                x_v = gate[16 + col];
            }
            for (uint32_t spins = 0;; spins++) {
                const bool ok = (((w.x ^ tg) | (w.y ^ tg) | (w.z ^ tg) | (w.w ^ tg)) & 3u) == 0;
                if (__all_sync(0xffffffffu, ok)) break;
                if (!ok) w = ld_relaxed_v4(src);
                if (spins > SPIN_LIMIT_ITERS) __trap();
            }
            float v0 = __uint_as_float(w.x & ~3u), v1 = __uint_as_float(w.y & ~3u);
            float v2 = __uint_as_float(w.z & ~3u), v3 = __uint_as_float(w.w & ~3u);
            const bool u16 = lane & 16, u8 = lane & 8;
            float a0 = (u16 ? v2 : v0) + __shfl_xor_sync(0xffffffffu, u16 ? v0 : v2, 16);
            float a1 = (u16 ? v3 : v1) + __shfl_xor_sync(0xffffffffu, u16 ? v1 : v3, 16);
            float a = (u8 ? a1 : a0) + __shfl_xor_sync(0xffffffffu, u8 ? a0 : a1, 8);
            a += __shfl_xor_sync(0xffffffffu, a, 4);
            float* fin = reinterpret_cast<float*>(smem + OFF_FIN);
            if (!(lane & 4)) fin[warp * 16 + 4 * (lane & 3) + (u16 ? 2 : 0) + (u8 ? 1 : 0)] = a;
            if (warp != 0) {
                __syncwarp();
                named_arrive(6, 128);
            } else {
                named_sync(6, 128);
                if (lane < 16) {
                    const float sum = (fin[lane] + fin[16 + lane]) + (fin[32 + lane] + fin[48 + lane]);
                    out[b * DM + h * 16 + col] = __float2bfloat16_rn(x_v + bf16r(bf16r(sum) * gate_v));
                }
            }
        }
        return;
    }

    const int hw = warp - 4;
    cluster_arrive_relaxed();
    const uint32_t tag = ld_epoch(late(epoch_) + blockIdx.x) + 1;
    cluster_wait();
    if (hw < 4) {
        const uint32_t abase = sbase + OFF_WQ + (uint32_t)((mi >> 1) * 8 + r) * 128 + (uint32_t)(((2 * hw + (mi & 1)) ^ r) << 4);
        const uint4* xs = reinterpret_cast<const uint4*>(smem + OFF_XS + ((g & 1) * 4 + t) * (68 * 4));
        float qa[4][4];
#pragma unroll
        for (int i = 0; i < 4; i++) { qa[i][0] = 0.f; qa[i][1] = 0.f; qa[i][2] = 0.f; qa[i][3] = 0.f; }
        named_sync(1, 192);
#pragma unroll
        for (int half = 0; half < 2; half++) {
            uint32_t xw[32];
#pragma unroll
            for (int i = 0; i < 8; i++) {
                const uint4 v = xs[half * 8 + i];
                xw[4 * i] = v.x; xw[4 * i + 1] = v.y; xw[4 * i + 2] = v.z; xw[4 * i + 3] = v.w;
            }
            mbar_wait(bar_wq + 8 * half, 0);
#pragma unroll
            for (int ks = 0; ks < 16; ks++) {
                uint32_t a[4];
                ldsm4t(a, abase + (half * 16 + ks) * 2048);
                mma16816(qa[ks & 3], a[0], a[1], a[2], a[3], xw[2 * ks], xw[2 * ks + 1]);
            }
        }
        const int ci = t;
        float v = 0.f;
#pragma unroll
        for (int i = 0; i < 4; i++) v = (ci == i) ? ((qa[0][i] + qa[1][i]) + (qa[2][i] + qa[3][i])) : v;
        const float vo = __shfl_xor_sync(0xffffffffu, v, 4);
        if (!(g & 1)) {
            const uint32_t dst = t & 1;
            const uint32_t word = (uint32_t)(rank * 32 + hw * 8 + (t >> 1) * 4 + (g >> 1));
            st_async_u32(mapa(sbase + OFF_QBF + word * 4, dst), pack_bf16(v, vo), mapa(bar_q, dst));
        }
        asm volatile("fence.proxy.async.shared::cta;" ::: "memory");
        __syncwarp();
        if (lane == 0) mbar_arrive(bar_scr);
    }
    if (hw == 0) {
        const int gg = lane & 7, f = lane >> 3;
        const Word2 w = poll_word2(fxp + ((f * NB + b) * 32 + h) * 8 + gg, tag, 500);
        float s0 = __uint_as_float((uint32_t)w.a), s1 = __uint_as_float((uint32_t)w.b);
        s0 += __shfl_xor_sync(0xffffffffu, s0, 8);  s1 += __shfl_xor_sync(0xffffffffu, s1, 8);
        s0 += __shfl_xor_sync(0xffffffffu, s0, 16); s1 += __shfl_xor_sync(0xffffffffu, s1, 16);
        if (lane < 8) {
            float* gate = reinterpret_cast<float*>(smem + OFF_GATE);
            gate[gg] = bf16r(silu_f(bf16r(s0)));
            gate[gg + 8] = bf16r(silu_f(bf16r(s1)));
            gate[16 + gg] = __bfloat162float(x[b * DM + h * 16 + gg]);
            gate[24 + gg] = __bfloat162float(x[b * DM + h * 16 + gg + 8]);
        }
        __syncwarp();
        named_arrive(5, 64);
    }

    {
        const uint32_t base = sbase + OFF_WO + hw * 2048 + (uint32_t)((mi >> 1) * 8 + r) * 128;
        const uint32_t xo = (uint32_t)((mi & 1) ^ r) << 4;
        const uint4* obp = reinterpret_cast<const uint4*>(ob + (g & 3) * 80 + t * 20);
        const int sdst = (t & 1) * 2 + (t >> 1);
        uint2* dst = reinterpret_cast<uint2*>(oxp + ((b * 32 + 4 * hw + sdst) * NH + h) * 4) + g;
        mbar_wait(bar_wo, 0);
        {
            uint32_t wf[7][4][4];
#pragma unroll
            for (int kk = 0; kk < 7; kk++)
#pragma unroll
                for (int s = 0; s < 4; s++) ldsm4t(wf[kk][s], base + kk * WO_PIECE_BYTES + (xo ^ (s << 5)));
            st_relaxed_v2(dst, (tag - 1) & 3, (tag - 1) & 3);
            named_sync(4, 384);
            float pacc[4][4];
#pragma unroll
            for (int s = 0; s < 4; s++) { pacc[s][0] = 0.f; pacc[s][1] = 0.f; pacc[s][2] = 0.f; pacc[s][3] = 0.f; }
            uint4 ow = obp[0];
#pragma unroll
            for (int s = 0; s < 4; s++) mma16816(pacc[s], wf[0][s][0], wf[0][s][1], wf[0][s][2], wf[0][s][3], ow.x, ow.y);
#pragma unroll
            for (int s = 0; s < 4; s++) mma16816(pacc[s], wf[1][s][0], wf[1][s][1], wf[1][s][2], wf[1][s][3], ow.z, ow.w);
#pragma unroll
            for (int i = 1; i < 3; i++) {
                ow = obp[i];
#pragma unroll
                for (int s = 0; s < 4; s++)
                    mma16816(pacc[s], wf[2 * i][s][0], wf[2 * i][s][1], wf[2 * i][s][2], wf[2 * i][s][3], ow.x, ow.y);
#pragma unroll
                for (int s = 0; s < 4; s++)
                    mma16816(pacc[s], wf[2 * i + 1][s][0], wf[2 * i + 1][s][1], wf[2 * i + 1][s][2], wf[2 * i + 1][s][3], ow.z, ow.w);
            }
            ow = obp[3];
#pragma unroll
            for (int s = 0; s < 4; s++) mma16816(pacc[s], wf[6][s][0], wf[6][s][1], wf[6][s][2], wf[6][s][3], ow.x, ow.y);
#pragma unroll
            for (int s = 0; s < 4; s++) {
                uint32_t w7[4];
                ldsm4t(w7, base + 7 * WO_PIECE_BYTES + (xo ^ (s << 5)));
                mma16816(pacc[s], w7[0], w7[1], w7[2], w7[3], ow.z, ow.w);
            }
            float v0[4], v1[4];
#pragma unroll
            for (int s = 0; s < 4; s++) { v0[s] = pacc[s][0] + pacc[s][1]; v1[s] = pacc[s][2] + pacc[s][3]; }
            const bool to = t & 1, th = t >> 1;
            const float ka0 = to ? v0[2] : v0[0], ka1 = to ? v0[3] : v0[1], kb0 = to ? v1[2] : v1[0], kb1 = to ? v1[3] : v1[1];
            const float sa0 = to ? v0[0] : v0[2], sa1 = to ? v0[1] : v0[3], sb0 = to ? v1[0] : v1[2], sb1 = to ? v1[1] : v1[3];
            const float sa = th ? sa1 : sa0, sb = th ? sb1 : sb0;
            const float ra = __shfl_xor_sync(0xffffffffu, sa, 1), rb = __shfl_xor_sync(0xffffffffu, sb, 1);
            const float o0 = (th ? ka1 : ka0) + ra, o1 = (th ? kb1 : kb0) + rb;
            const uint32_t tg = tag & 3;
            st_relaxed_v2(dst, (__float_as_uint(o0) & ~3u) | tg, (__float_as_uint(o1) & ~3u) | tg);
        }
    }
}

}

extern "C" void kernel_launch(void* const* d_in, const int* in_sizes, int n_in, void* d_out, int out_size) {
    (void)in_sizes; (void)n_in; (void)out_size;
    const __nv_bfloat16* x = (const __nv_bfloat16*)d_in[0];
    const __nv_bfloat16* kc = (const __nv_bfloat16*)d_in[1];
    const __nv_bfloat16* vc = (const __nv_bfloat16*)d_in[2];
    const __nv_bfloat16* wq = (const __nv_bfloat16*)d_in[3];
    const __nv_bfloat16* wo = (const __nv_bfloat16*)d_in[4];
    const __nv_bfloat16* w1 = (const __nv_bfloat16*)d_in[6];
    const __nv_bfloat16* w2 = (const __nv_bfloat16*)d_in[7];
    typedef CUresult (*EncodeFn)(CUtensorMap*, CUtensorMapDataType, cuuint32_t, void*, const cuuint64_t*, const cuuint64_t*,
                                 const cuuint32_t*, const cuuint32_t*, CUtensorMapInterleave, CUtensorMapSwizzle,
                                 CUtensorMapL2promotion, CUtensorMapFloatOOBfill);
    static unsigned int *epoch = nullptr, *progp = nullptr;
    static uint4* oxp = nullptr;
    static Word2* fxp = nullptr;
    static EncodeFn encode = nullptr;
    if (!epoch) {
        cudaFuncSetAttribute(fused_decode_kernel, cudaFuncAttributeMaxDynamicSharedMemorySize, SMEM_BYTES);
        void* fn = nullptr;
        cudaDriverEntryPointQueryResult qr;
        cudaGetDriverEntryPoint("cuTensorMapEncodeTiled", &fn, cudaEnableDefault, &qr);
        encode = (EncodeFn)fn;
        cudaGetSymbolAddress((void**)&oxp, g_ox);
        cudaGetSymbolAddress((void**)&fxp, g_fx);
        cudaGetSymbolAddress((void**)&progp, g_prog);
        cudaGetSymbolAddress((void**)&epoch, g_epoch);
    }
    CUtensorMap wq_map, wo_map;
    const cuuint32_t estride[2] = {1, 1};
    {
        const cuuint64_t gdim[2] = {(cuuint64_t)(NH * DH), (cuuint64_t)DM}, gstride[1] = {(cuuint64_t)(NH * DH * 2)};
        const cuuint32_t box[2] = {64, 256};
        encode(&wq_map, CU_TENSOR_MAP_DATA_TYPE_BFLOAT16, 2, (void*)wq, gdim, gstride, box, estride, CU_TENSOR_MAP_INTERLEAVE_NONE,
               CU_TENSOR_MAP_SWIZZLE_128B, CU_TENSOR_MAP_L2_PROMOTION_NONE, CU_TENSOR_MAP_FLOAT_OOB_FILL_NONE);
    }
    {
        const cuuint64_t gdim[3] = {64, (cuuint64_t)(NH * DH), 8}, gstride[2] = {(cuuint64_t)(DM * 2), 128};
        const cuuint32_t box[3] = {64, 16, 8}, es3[3] = {1, 1, 1};
        encode(&wo_map, CU_TENSOR_MAP_DATA_TYPE_BFLOAT16, 3, (void*)wo, gdim, gstride, box, es3, CU_TENSOR_MAP_INTERLEAVE_NONE,
               CU_TENSOR_MAP_SWIZZLE_128B, CU_TENSOR_MAP_L2_PROMOTION_NONE, CU_TENSOR_MAP_FLOAT_OOB_FILL_NONE);
    }
    fused_decode_kernel<<<NCTA, NTHREADS, SMEM_BYTES, cudaStreamPerThread>>>(x, kc, vc, (__nv_bfloat16*)d_out, w1, w2,
                                                                             epoch, progp, oxp, fxp, wq_map, wo_map);
}
```

```cpp
#include <cuda_runtime.h>
#include <cuda.h>
#include <cuda_bf16.h>
#include <stdint.h>

namespace {

constexpr int NB = 4, DM = 512, NH = 32, SK = 8192, DH = 128, FF = 1376;
constexpr int NATT = NB * NH;
constexpr int NFFN = 4;
constexpr int NCTA = NATT + NFFN;
constexpr int NTHREADS = 416;

constexpr int TILE = 64;
constexpr int SLOT_BYTES = TILE * DH * 2;
constexpr int NSLOT = 6;
constexpr int WIN_BASE = 4, WIN_MIN = 1, WIN_MAX = NSLOT;
constexpr int WIN_P_SHIFT = 8;
constexpr int WIN_I_SHIFT = 4;
constexpr int NSTAGE = SK / TILE;
constexpr int NSEQ = 2 * NSTAGE;
constexpr int RING_BYTES = NSLOT * SLOT_BYTES;
constexpr int WO_BYTES = DH * DM * 2;
constexpr int WO_PIECES = 8;
constexpr int WO_PIECE_BYTES = WO_BYTES / WO_PIECES;

constexpr int OFF_WO = RING_BYTES;
constexpr int OFF_WQ = OFF_WO;
constexpr int WQ_BYTES = DM * 128;
constexpr int OFF_XS = OFF_WO + WQ_BYTES;
constexpr int OFF_MISC = OFF_WO + WO_BYTES;
constexpr int OFF_OB = OFF_MISC;
constexpr int OFF_ML = OFF_OB + 1280;
constexpr int OFF_QBF = OFF_ML + 32;
constexpr int OFF_GATE = OFF_QBF + 256;
constexpr int OFF_FIN = OFF_GATE + 128;
constexpr int OFF_BAR = OFF_FIN + 256;
constexpr int SMEM_BYTES = OFF_BAR + 160;
static_assert(SMEM_BYTES <= 232448, "smem");
static_assert(DM * FF * 2 == NATT * 86 * 128 && NH * DH * DM * 2 == NATT * 256 * 128, "prefetch shares");

constexpr int FSL = FF / NFFN;
constexpr int FOFF_XN = 0;
constexpr int FOFF_HP = 8192;
constexpr int FOFF_HS = FOFF_HP + 8 * 4 * FSL * 4;
constexpr int FOFF_OP = FOFF_HS + FSL * 16;

struct __align__(16) Word2 { unsigned long long a, b; };

__device__ unsigned int g_epoch[NCTA];
__device__ unsigned int g_prog[2];
__device__ uint4 g_ox[NB][32][NH][4];
__device__ Word2 g_fx[NFFN][NB][32][8];


__device__ __forceinline__ uint32_t smem_u32(const void* p) { return (uint32_t)__cvta_generic_to_shared(p); }

__device__ __forceinline__ void mbar_init(uint32_t bar, uint32_t count) {
    asm volatile("mbarrier.init.shared::cta.b64 [%0], %1;" ::"r"(bar), "r"(count) : "memory");
}
__device__ __forceinline__ void mbar_expect_tx(uint32_t bar, uint32_t bytes) {
    asm volatile("mbarrier.arrive.expect_tx.shared::cta.b64 _, [%0], %1;" ::"r"(bar), "r"(bytes) : "memory");
}
__device__ __forceinline__ void mbar_arrive(uint32_t bar) {
    asm volatile("mbarrier.arrive.shared::cta.b64 _, [%0];" ::"r"(bar) : "memory");
}
__device__ __forceinline__ bool mbar_try(uint32_t bar, uint32_t parity) {
    uint32_t ok;
    asm volatile("{\n.reg .pred p;\nmbarrier.try_wait.parity.shared::cta.b64 p, [%1], %2;\nselp.u32 %0, 1, 0, p;\n}"
                 : "=r"(ok) : "r"(bar), "r"(parity) : "memory");
    return ok != 0;
}
constexpr long long SPIN_LIMIT_CLK = 4000000000LL;
constexpr uint32_t SPIN_LIMIT_ITERS = 1u << 23;
__device__ __forceinline__ void mbar_wait(uint32_t bar, uint32_t parity) {
    if (mbar_try(bar, parity)) return;
    long long t0 = clock64();
    while (!mbar_try(bar, parity)) {
        if (clock64() - t0 > SPIN_LIMIT_CLK) __trap();
    }
}
__device__ __forceinline__ void bulk_load(uint32_t dst, const void* src, uint32_t bytes, uint32_t bar, uint64_t pol) {
    asm volatile("cp.async.bulk.shared::cluster.global.mbarrier::complete_tx::bytes.L2::cache_hint [%0], [%1], %2, [%3], %4;"
                 ::"r"(dst), "l"(src), "r"(bytes), "r"(bar), "l"(pol) : "memory");
}
__device__ __forceinline__ void tensor_load_2d(uint32_t dst, const CUtensorMap* tm, int c0, int c1, uint32_t bar) {
    asm volatile("cp.async.bulk.tensor.2d.shared::cluster.global.mbarrier::complete_tx::bytes [%0], [%1, {%3, %4}], [%2];"
                 ::"r"(dst), "l"(tm), "r"(bar), "r"(c0), "r"(c1) : "memory");
}
__device__ __forceinline__ void tensor_load_3d(uint32_t dst, const CUtensorMap* tm, int c0, int c1, int c2, uint32_t bar) {
    asm volatile("cp.async.bulk.tensor.3d.shared::cluster.global.mbarrier::complete_tx::bytes [%0], [%1, {%3, %4, %5}], [%2];"
                 ::"r"(dst), "l"(tm), "r"(bar), "r"(c0), "r"(c1), "r"(c2) : "memory");
}
__device__ __forceinline__ void prefetch_line(const void* p) { asm volatile("prefetch.global.L2 [%0];" ::"l"(p) : "memory"); }
__device__ __forceinline__ void named_sync(int id, int n) { asm volatile("bar.sync %0, %1;" ::"r"(id), "r"(n) : "memory"); }
__device__ __forceinline__ void named_arrive(int id, int n) { asm volatile("bar.arrive %0, %1;" ::"r"(id), "r"(n) : "memory"); }

__device__ __forceinline__ void cluster_arrive_relaxed() { asm volatile("barrier.cluster.arrive.relaxed.aligned;" ::: "memory"); }
__device__ __forceinline__ void cluster_wait() { asm volatile("barrier.cluster.wait.aligned;" ::: "memory"); }
__device__ __forceinline__ uint32_t mapa(uint32_t addr, uint32_t rank) {
    uint32_t r;
    asm("mapa.shared::cluster.u32 %0, %1, %2;" : "=r"(r) : "r"(addr), "r"(rank));
    return r;
}
__device__ __forceinline__ void st_async_u32(uint32_t addr, uint32_t v, uint32_t bar) {
    asm volatile("st.async.weak.shared::cluster.mbarrier::complete_tx::bytes.u32 [%0], %1, [%2];" ::"r"(addr), "r"(v), "r"(bar) : "memory");
}

__device__ __forceinline__ void ldsm4(uint32_t (&r)[4], uint32_t addr) {
    asm volatile("ldmatrix.sync.aligned.m8n8.x4.shared.b16 {%0,%1,%2,%3}, [%4];"
                 : "=r"(r[0]), "=r"(r[1]), "=r"(r[2]), "=r"(r[3]) : "r"(addr) : "memory");
}
__device__ __forceinline__ void ldsm4t(uint32_t (&r)[4], uint32_t addr) {
    asm volatile("ldmatrix.sync.aligned.m8n8.x4.trans.shared.b16 {%0,%1,%2,%3}, [%4];"
                 : "=r"(r[0]), "=r"(r[1]), "=r"(r[2]), "=r"(r[3]) : "r"(addr) : "memory");
}
__device__ __forceinline__ void mma16816(float (&c)[4], uint32_t a0, uint32_t a1, uint32_t a2, uint32_t a3, uint32_t b0, uint32_t b1) {
    asm volatile("mma.sync.aligned.m16n8k16.row.col.f32.bf16.bf16.f32 {%0,%1,%2,%3}, {%4,%5,%6,%7}, {%8,%9}, {%0,%1,%2,%3};"
                 : "+f"(c[0]), "+f"(c[1]), "+f"(c[2]), "+f"(c[3])
                 : "r"(a0), "r"(a1), "r"(a2), "r"(a3), "r"(b0), "r"(b1));
}
__device__ __forceinline__ uint32_t pack_bf16(float lo, float hi) {
    uint32_t r;
    asm("cvt.rn.bf16x2.f32 %0, %1, %2;" : "=r"(r) : "f"(hi), "f"(lo));
    return r;
}
__device__ __forceinline__ float bf_lo(uint32_t u) { return __uint_as_float(u << 16); }
__device__ __forceinline__ float bf_hi(uint32_t u) { return __uint_as_float(u & 0xffff0000u); }
__device__ __forceinline__ float bf16r(float x) { return __bfloat162float(__float2bfloat16_rn(x)); }
__device__ __forceinline__ float ex2(float x) {
    float y;
    asm("ex2.approx.ftz.f32 %0, %1;" : "=f"(y) : "f"(x));
    return y;
}
__device__ __forceinline__ float silu_f(float x) { return x / (1.0f + expf(-x)); }

__device__ __forceinline__ uint4 ldg_nc(const void* p) {
    uint4 v;
    asm volatile("ld.global.nc.L1::no_allocate.v4.u32 {%0,%1,%2,%3}, [%4];" : "=r"(v.x), "=r"(v.y), "=r"(v.z), "=r"(v.w) : "l"(p));
    return v;
}
__device__ __forceinline__ Word2 ld_word2(const Word2* p) {
    Word2 v;
    asm volatile("ld.relaxed.gpu.global.v2.b64 {%0,%1}, [%2];" : "=l"(v.a), "=l"(v.b) : "l"(p) : "memory");
    return v;
}
__device__ __forceinline__ void st_word2(Word2* p, unsigned long long a, unsigned long long b) {
    asm volatile("st.relaxed.gpu.global.v2.b64 [%0], {%1,%2};" ::"l"(p), "l"(a), "l"(b) : "memory");
}
__device__ __forceinline__ uint4 ld_relaxed_v4(const uint4* p) {
    uint4 v;
    asm volatile("ld.relaxed.gpu.global.v4.u32 {%0,%1,%2,%3}, [%4];" : "=r"(v.x), "=r"(v.y), "=r"(v.z), "=r"(v.w) : "l"(p) : "memory");
    return v;
}
__device__ __forceinline__ void st_relaxed_v2(uint2* p, uint32_t a, uint32_t b) {
    asm volatile("st.relaxed.gpu.global.v2.u32 [%0], {%1,%2};" ::"l"(p), "r"(a), "r"(b) : "memory");
}
template <typename T>
__device__ __forceinline__ T* late(T* p) { asm volatile("" : "+l"(p) :: "memory"); return p; }
__device__ __forceinline__ uint32_t ld_epoch(const unsigned int* p) {
    uint32_t v;
    asm volatile("ld.relaxed.gpu.global.u32 %0, [%1];" : "=r"(v) : "l"(p) : "memory");
    return v;
}
__device__ __forceinline__ unsigned long long mkword(uint32_t payload, uint32_t tag) {
    return ((unsigned long long)tag << 32) | payload;
}
__device__ __forceinline__ bool word2_ok(const Word2& w, uint32_t tag) {
    return (uint32_t)(w.a >> 32) == tag && (uint32_t)(w.b >> 32) == tag;
}
__device__ __forceinline__ Word2 poll_word2(const Word2* p, uint32_t tag, unsigned sleep_ns) {
    Word2 w = ld_word2(p);
    if (__all_sync(0xffffffffu, word2_ok(w, tag))) return w;
    long long t0 = clock64();
    while (true) {
        if (sleep_ns) __nanosleep(sleep_ns);
        w = ld_word2(p);
        if (__all_sync(0xffffffffu, word2_ok(w, tag))) return w;
        if (clock64() - t0 > SPIN_LIMIT_CLK) __trap();
    }
}

__device__ __forceinline__ int tile_of_stage(int s) { return (s & ~7) | ((s & 3) << 1) | ((s >> 2) & 1); }

__device__ __forceinline__ void layernorm_row(const uint4 a, const uint4 b, float (&v)[16]) {
    v[0] = bf_lo(a.x); v[1] = bf_hi(a.x); v[2] = bf_lo(a.y); v[3] = bf_hi(a.y);
    v[4] = bf_lo(a.z); v[5] = bf_hi(a.z); v[6] = bf_lo(a.w); v[7] = bf_hi(a.w);
    v[8] = bf_lo(b.x); v[9] = bf_hi(b.x); v[10] = bf_lo(b.y); v[11] = bf_hi(b.y);
    v[12] = bf_lo(b.z); v[13] = bf_hi(b.z); v[14] = bf_lo(b.w); v[15] = bf_hi(b.w);
    float s = 0.f;
#pragma unroll
    for (int i = 0; i < 16; i++) s += v[i];
#pragma unroll
    for (int o = 16; o > 0; o >>= 1) s += __shfl_xor_sync(0xffffffffu, s, o);
    const float mean = s * (1.0f / DM);
    float q = 0.f;
#pragma unroll
    for (int i = 0; i < 16; i++) { float d = v[i] - mean; q += d * d; }
#pragma unroll
    for (int o = 16; o > 0; o >>= 1) q += __shfl_xor_sync(0xffffffffu, q, o);
    const float mb = bf16r(mean);
    const float vb = bf16r(q * (1.0f / DM));
    const float den = bf16r(sqrtf(bf16r(vb + 1e-5f)));
#pragma unroll
    for (int i = 0; i < 16; i++) v[i] = bf16r(bf16r(v[i] - mb) / den);
}

__device__ __forceinline__ void ffn_gemv(float (&acc)[4][8], const __nv_bfloat16* __restrict__ wp, int ld,
                                         const float4* act, int r0, int r1) {
    for (int r = r0; r < r1; r += 16) {
        uint4 w[16];
#pragma unroll
        for (int u = 0; u < 16; u++) w[u] = (r + u < r1) ? ldg_nc(wp + (size_t)(r + u) * ld) : make_uint4(0, 0, 0, 0);
#pragma unroll
        for (int u = 0; u < 16; u++) {
            const float4 xv = act[min(r + u, r1 - 1)];
            const float wf[8] = {bf_lo(w[u].x), bf_hi(w[u].x), bf_lo(w[u].y), bf_hi(w[u].y),
                                 bf_lo(w[u].z), bf_hi(w[u].z), bf_lo(w[u].w), bf_hi(w[u].w)};
#pragma unroll
            for (int e = 0; e < 8; e++) {
                acc[0][e] = fmaf(xv.x, wf[e], acc[0][e]); acc[1][e] = fmaf(xv.y, wf[e], acc[1][e]);
                acc[2][e] = fmaf(xv.z, wf[e], acc[2][e]); acc[3][e] = fmaf(xv.w, wf[e], acc[3][e]);
            }
        }
    }
}

__device__ __forceinline__ void ffn_cta(unsigned char* smem, int f, const __nv_bfloat16* __restrict__ x,
                                        const __nv_bfloat16* __restrict__ w1, const __nv_bfloat16* __restrict__ w2,
                                        unsigned int* epoch, Word2* fxp) {
    const int tid = threadIdx.x, warp = tid >> 5, lane = tid & 31;
    float* xn4 = reinterpret_cast<float*>(smem + FOFF_XN);
    float* hp = reinterpret_cast<float*>(smem + FOFF_HP);
    float4* hs = reinterpret_cast<float4*>(smem + FOFF_HS);
    float* op = reinterpret_cast<float*>(smem + FOFF_OP);

    const uint32_t tag = ld_epoch(epoch + blockIdx.x) + 1;
    if (warp < 4) {
        const uint4* xr = reinterpret_cast<const uint4*>(x + warp * DM);
        float v[16];
        layernorm_row(ldg_nc(xr + lane), ldg_nc(xr + 32 + lane), v);
#pragma unroll
        for (int i = 0; i < 16; i++) xn4[((i < 8) ? (lane * 8 + i) : (248 + lane * 8 + i)) * 4 + warp] = v[i];
    }
    __syncthreads();
    if (tid == 0) epoch[blockIdx.x] = tag;

    float acc[4][8];
    if (tid < 344) {
        const int cg = tid % 43, ks = tid / 43;
#pragma unroll
        for (int b = 0; b < 4; b++)
#pragma unroll
            for (int e = 0; e < 8; e++) acc[b][e] = 0.f;
        ffn_gemv(acc, w1 + f * FSL + cg * 8, FF, reinterpret_cast<const float4*>(xn4), ks * 64, ks * 64 + 64);
#pragma unroll
        for (int b = 0; b < 4; b++)
#pragma unroll
            for (int e = 0; e < 8; e++) hp[(ks * 4 + b) * FSL + cg * 8 + e] = acc[b][e];
    }
    __syncthreads();
    for (int i = tid; i < 4 * FSL; i += NTHREADS) {
        const int b = i / FSL, c = i % FSL;
        float s = 0.f;
#pragma unroll
        for (int ks = 0; ks < 8; ks++) s += hp[(ks * 4 + b) * FSL + c];
        reinterpret_cast<float*>(hs)[c * 4 + b] = bf16r(silu_f(bf16r(s)));
    }
    __syncthreads();
    if (tid < 384) {
        const int cg = tid & 63, ks = tid >> 6;
#pragma unroll
        for (int b = 0; b < 4; b++)
#pragma unroll
            for (int e = 0; e < 8; e++) acc[b][e] = 0.f;
        ffn_gemv(acc, w2 + (size_t)(f * FSL) * DM + cg * 8, DM, hs, ks * 58, min(ks * 58 + 58, FSL));
#pragma unroll
        for (int b = 0; b < 4; b++)
#pragma unroll
            for (int e = 0; e < 8; e++) op[(ks * 4 + b) * DM + cg * 8 + e] = acc[b][e];
    }
    __syncthreads();
    for (int i = tid; i < NB * 32 * 8; i += NTHREADS) {
        const int b = i >> 8, hh = (i >> 3) & 31, g = i & 7;
        const int c0 = hh * 16 + g;
        float s0 = 0.f, s1 = 0.f;
#pragma unroll
        for (int ks = 0; ks < 6; ks++) { s0 += op[(ks * 4 + b) * DM + c0]; s1 += op[(ks * 4 + b) * DM + c0 + 8]; }
        st_word2(fxp + ((f * NB + b) * 32 + hh) * 8 + g, mkword(__float_as_uint(s0), tag), mkword(__float_as_uint(s1), tag));
    }
}

template <int NT>
__device__ __forceinline__ void diag_reduce(const float (&acc)[NT][4], float (&u)[2 * NT]) {
#pragma unroll
    for (int s = 0; s < NT; s++) {
        u[2 * s] = acc[s][0] + acc[s][3];
        u[2 * s + 1] = acc[s][2] + acc[s][1];
    }
#pragma unroll
    for (int L = 0; L < 2 * NT; L++)
        if (!(L & 2)) u[L] += __shfl_xor_sync(0xffffffffu, u[L ^ 2], 1);
#pragma unroll
    for (int L = 0; L < 2 * NT; L++)
        if (!(L & 6)) u[L] += __shfl_xor_sync(0xffffffffu, u[L ^ 4], 2);
}

__device__ __forceinline__ float combine_stats(float m, float l, float* ml, int warp, int lane) {
    const float LOG2E = 1.4426950408889634f;
#pragma unroll
    for (int o = 16; o > 0; o >>= 1) l += __shfl_xor_sync(0xffffffffu, l, o);
    if (lane == 0) *reinterpret_cast<float2*>(ml + warp * 2) = make_float2(m, l);
    named_sync(3, 128);
    const float4 ml01 = *reinterpret_cast<const float4*>(ml), ml23 = *reinterpret_cast<const float4*>(ml + 4);
    const float M = fmaxf(fmaxf(ml01.x, ml01.z), fmaxf(ml23.x, ml23.z));
    const float L = ex2((ml01.x - M) * LOG2E) * ml01.y + ex2((ml01.z - M) * LOG2E) * ml01.w +
                    ex2((ml23.x - M) * LOG2E) * ml23.y + ex2((ml23.z - M) * LOG2E) * ml23.w;
    return ex2((m - M) * LOG2E) / L;
}

__device__ __forceinline__ void publish_partial(const float (&acc)[8][4], float cw, uint32_t* ob, int warp, int g, int t) {
    float u[16];
    diag_reduce<8>(acc, u);
    const bool og = g & 1;
    const float k0 = (og ? u[8] : u[0]) * cw, k1 = (og ? u[9] : u[1]) * cw;
    const float s0 = (og ? u[0] : u[8]) * cw, s1 = (og ? u[1] : u[9]) * cw;
    const float r0 = __shfl_xor_sync(0xffffffffu, s0, 4), r1 = __shfl_xor_sync(0xffffffffu, s1, 4);
    const uint32_t w0 = og ? pack_bf16(r0, k0) : pack_bf16(k0, r0);
    const uint32_t w1 = og ? pack_bf16(r1, k1) : pack_bf16(k1, r1);
    *reinterpret_cast<uint2*>(ob + warp * 80 + (g >> 1) * 20 + (og ? 8 : 0) + 2 * t) = make_uint2(w0, w1);
    __syncwarp();
}

__global__ void __cluster_dims__(2, 1, 1) __launch_bounds__(NTHREADS, 1)
fused_decode_kernel(const __nv_bfloat16* __restrict__ x, const __nv_bfloat16* __restrict__ kc,
                    const __nv_bfloat16* __restrict__ vc, __nv_bfloat16* __restrict__ out,
                    const __nv_bfloat16* __restrict__ w1, const __nv_bfloat16* __restrict__ w2,
                    const __nv_bfloat16* __restrict__ wo,
                    unsigned int* __restrict__ epoch_, unsigned int* __restrict__ progp,
                    uint4* __restrict__ oxp, Word2* __restrict__ fxp,
                    const __grid_constant__ CUtensorMap wq_map, const __grid_constant__ CUtensorMap wo_map) {
    extern __shared__ __align__(1024) unsigned char smem[];
    const int tid = threadIdx.x, warp = tid >> 5, lane = tid & 31;

    if (blockIdx.x >= NATT) {
        ffn_cta(smem, blockIdx.x - NATT, x, w1, w2, epoch_, fxp);
        return;
    }

    const int a_idx = blockIdx.x;
    const int rank = a_idx & 1, h = (a_idx >> 1) & 31, bp = a_idx >> 6;
    const int b = 2 * bp + rank, bh = b * NH + h;
    const uint32_t sbase = smem_u32(smem);
    const uint32_t bar_full = sbase + OFF_BAR;
    const uint32_t bar_empty = bar_full + 8 * NSLOT;
    const uint32_t bar_wo = bar_empty + 8 * NSLOT;
    const uint32_t bar_q = bar_wo + 8;
    const uint32_t bar_scr = bar_q + 8;
    const uint32_t bar_wq = bar_scr + 8;

    if (warp == 12) {
        const char* kp = reinterpret_cast<const char*>(kc) + (size_t)bh * SK * DH * 2;
        const char* vp = reinterpret_cast<const char*>(vc) + (size_t)bh * SK * DH * 2;
        uint64_t pol;
        asm volatile("createpolicy.fractional.L2::evict_first.b64 %0, 1.0;" : "=l"(pol));
        if (lane == 0) {
            mbar_init(bar_wq, 1);
            mbar_init(bar_wq + 8, 1);
#pragma unroll
            for (int i = 0; i < 2; i++) {
                mbar_expect_tx(bar_wq + 8 * i, WQ_BYTES / 2);
                tensor_load_2d(sbase + OFF_WQ + i * (WQ_BYTES / 2), &wq_map, h * DH + rank * 64, i * 256, bar_wq + 8 * i);
            }
            for (int s = 0; s < NSLOT; s++) mbar_init(bar_full + 8 * s, 1);
            for (int s = 0; s < WIN_BASE; s++) {
                mbar_expect_tx(bar_full + 8 * s, SLOT_BYTES);
                bulk_load(sbase + s * SLOT_BYTES, ((s & 1) ? vp : kp) + (size_t)tile_of_stage(s >> 1) * SLOT_BYTES, SLOT_BYTES, bar_full + 8 * s, pol);
            }
            for (int s = 0; s < NSLOT; s++) mbar_init(bar_empty + 8 * s, 4);
            mbar_init(bar_wo, 1);
            mbar_init(bar_q, 1);
            mbar_init(bar_scr, 4);
            mbar_expect_tx(bar_q, 256);
            asm volatile("fence.mbarrier_init.release.cluster;" ::: "memory");
            asm volatile("prefetch.tensormap [%0];" ::"l"(&wo_map) : "memory");
        }
        __syncwarp();
        cluster_arrive_relaxed();
        unsigned int* epoch = late(epoch_);
        const uint32_t tag = ld_epoch(epoch + blockIdx.x) + 1;
        cluster_wait();
        if (lane == 0) {
            unsigned int* prog = progp + (tag & 1);
            if (blockIdx.x == 0) progp[(tag + 1) & 1] = 0;
            int win = WIN_BASE, integ = 0, nupd = 0;
            uint32_t pend = 0;
            int slot = WIN_BASE % NSLOT;
            int released = -1, rslot = 0;
            uint32_t rph = 0;
            for (int seq = WIN_BASE; seq < NSEQ; seq++) {
                if (!(seq & 1)) {
                    if (nupd > 0) {
                        int ctl = (int)(2 * pend) - 2 * (nupd - 1) * NATT - 128;
                        integ = min(max(integ + ctl, -(3 << (WIN_P_SHIFT + WIN_I_SHIFT))), 3 << (WIN_P_SHIFT + WIN_I_SHIFT));
                        ctl += (integ >> WIN_I_SHIFT) + 32 + 64 * (nupd & 3);
                        win = min(max(WIN_BASE + (ctl >> WIN_P_SHIFT), WIN_MIN), WIN_MAX);
                    }
                    pend = atomicAdd(prog, 1u);
                    nupd++;
                }
                while (released < seq - win) {
                    released++;
                    mbar_wait(bar_empty + 8 * rslot, rph);
                    if (++rslot == NSLOT) { rslot = 0; rph ^= 1; }
                }
                mbar_expect_tx(bar_full + 8 * slot, SLOT_BYTES);
                bulk_load(sbase + slot * SLOT_BYTES, ((seq & 1) ? vp : kp) + (size_t)tile_of_stage(seq >> 1) * SLOT_BYTES, SLOT_BYTES,
                          bar_full + 8 * slot, pol);
                if (seq >= 8 && seq < 8 + 2 * WO_PIECES && !(seq & 1)) {
                    const int p = (seq - 8) >> 1;
                    if (p == 0) { mbar_wait(bar_scr, 0); mbar_expect_tx(bar_wo, WO_BYTES); }
                    tensor_load_3d(sbase + OFF_WO + p * WO_PIECE_BYTES, &wo_map, 0, h * DH + p * 16, 0, bar_wo);
                }
                if (++slot == NSLOT) slot = 0;
            }
            epoch[blockIdx.x] = tag;
        }
        return;
    }

    const int g = lane >> 2, t = lane & 3;
    const int mi = lane >> 3, r = lane & 7;
    uint32_t* ob = reinterpret_cast<uint32_t*>(smem + OFF_OB);

    if (warp < 4) {
        if (warp < 2) {
            const uint4* xr = reinterpret_cast<const uint4*>(x + (2 * bp + warp) * DM);
            const uint4 xa = ldg_nc(xr + lane), xb = ldg_nc(xr + 32 + lane);
            cluster_arrive_relaxed();
            float v[16];
            layernorm_row(xa, xb, v);
            uint32_t* xs = reinterpret_cast<uint32_t*>(smem + OFF_XS) + warp * (4 * 68);
#pragma unroll
            for (int j = 0; j < 4; j++) {
                xs[j * 68 + lane] = pack_bf16(v[2 * j], v[2 * j + 1]);
                xs[j * 68 + 32 + lane] = pack_bf16(v[8 + 2 * j], v[8 + 2 * j + 1]);
            }
            __syncwarp();
            named_arrive(1, 192);
        } else {
            cluster_arrive_relaxed();
        }
        const uint32_t tag = ld_epoch(late(epoch_) + blockIdx.x) + 1;
        cluster_wait();
        mbar_wait(bar_q, 0);
        const uint32_t* qbf = reinterpret_cast<const uint32_t*>(smem + OFF_QBF);
        uint32_t qf[16];
#pragma unroll
        for (int L = 0; L < 16; L++) qf[L] = qbf[((L & 8) | ((L & 7) ^ g)) * 4 + t];

        const uint32_t rowoff = (uint32_t)(warp * 16 + (mi >> 1) * 8 + r) * 256;
        uint32_t coff[4];
#pragma unroll
        for (int j = 0; j < 4; j++) coff[j] = rowoff + ((((mi & 1) ^ r) ^ (2 * j)) << 4);

        const bool valid = (t == (g >> 1));
        const bool odd = g & 1;
        const uint32_t sel0 = odd ? 0x1044u : 0x4410u, sel1 = odd ? 0x3244u : 0x4432u;
        const float NEG_INF = __int_as_float(0xff800000);
        const float SCALE = 0.08838834764831845f, LOG2E = 1.4426950408889634f;

        float acc[8][4];
#pragma unroll
        for (int s = 0; s < 8; s++) { acc[s][0] = 0.f; acc[s][1] = 0.f; acc[s][2] = 0.f; acc[s][3] = 0.f; }
        float m = NEG_INF, msub = 0.f, l = 0.f, cw = 0.f;
        float* ml = reinterpret_cast<float*>(smem + OFF_ML);
        int slot = 0;
        uint32_t ph = 0;

        for (int st = 0; st < NSTAGE; st++) {
            uint32_t a[8][4];
            const uint32_t kb = sbase + slot * SLOT_BYTES;
            mbar_wait(bar_full + 8 * slot, ph);
#pragma unroll
            for (int s = 0; s < 8; s++) ldsm4(a[s], kb + coff[s & 3] + (s >> 2) * 128);
            float c0[4] = {0.f, 0.f, 0.f, 0.f}, c1[4] = {0.f, 0.f, 0.f, 0.f};
#pragma unroll
            for (int s = 0; s < 8; s += 2) {
                mma16816(c0, a[s][0], a[s][2], a[s][1], a[s][3], qf[2 * s], qf[2 * s + 1]);
                mma16816(c1, a[s + 1][0], a[s + 1][2], a[s + 1][1], a[s + 1][3], qf[2 * s + 2], qf[2 * s + 3]);
            }
            __syncwarp();
            if (lane == 0) mbar_arrive(bar_empty + 8 * slot);
            if (++slot == NSLOT) { slot = 0; ph ^= 1; }

            float sa = odd ? (c0[1] + c1[1]) : (c0[0] + c1[0]);
            float sb = odd ? (c0[3] + c1[3]) : (c0[2] + c1[2]);
            uint32_t pr = pack_bf16(sa, sb);
            pr = pack_bf16(bf_lo(pr) * SCALE, bf_hi(pr) * SCALE);
            sa = valid ? bf_lo(pr) : NEG_INF;
            sb = valid ? bf_hi(pr) : NEG_INF;
            const float tmax = fmaxf(sa, sb);
            if (__any_sync(0xffffffffu, tmax > m)) {
                float nm = tmax;
#pragma unroll
                for (int o = 16; o > 0; o >>= 1) nm = fmaxf(nm, __shfl_xor_sync(0xffffffffu, nm, o));
                nm = fmaxf(nm, m);
                const float alpha = ex2((m - nm) * LOG2E);
#pragma unroll
                for (int s = 0; s < 8; s++) { acc[s][0] *= alpha; acc[s][1] *= alpha; acc[s][2] *= alpha; acc[s][3] *= alpha; }
                l *= alpha;
                m = nm; msub = nm;
            }
            const float pa = ex2((sa - msub) * LOG2E), pb = ex2((sb - msub) * LOG2E);
            l += pa + pb;
            const uint32_t pp = pack_bf16(pa, pb);
            const uint32_t b0 = __byte_perm(pp, 0, sel0), b1 = __byte_perm(pp, 0, sel1);

            if (st == NSTAGE - 1) cw = combine_stats(m, l, ml, warp, lane);

            const uint32_t vb = sbase + slot * SLOT_BYTES;
            mbar_wait(bar_full + 8 * slot, ph);
#pragma unroll
            for (int s = 0; s < 8; s++) ldsm4t(a[s], vb + coff[s & 3] + (s >> 2) * 128);
#pragma unroll
            for (int s = 0; s < 8; s++) mma16816(acc[s], a[s][0], a[s][1], a[s][2], a[s][3], b0, b1);
            __syncwarp();
            if (lane == 0) mbar_arrive(bar_empty + 8 * slot);
            if (++slot == NSLOT) { slot = 0; ph ^= 1; }

        }
        publish_partial(acc, cw, ob, warp, g, t);
        named_arrive(4, 384);

        {
            const uint4* src = oxp + ((b * 32 + h) * NH + warp * 8 + (lane >> 2)) * 4 + (lane & 3);
            const uint32_t tg = tag & 3;
            uint4 w = ld_relaxed_v4(src);
            const int col = ((lane >> 1) & 7) + 8 * (lane & 1);
            float gate_v = 0.f, x_v = 0.f;
            if (warp == 0) {
                named_sync(5, 64);
                const float* gate = reinterpret_cast<const float*>(smem + OFF_GATE);
                gate_v = gate[col];
                x_v = gate[16 + col];
            }
            for (uint32_t spins = 0;; spins++) {
                const bool ok = (((w.x ^ tg) | (w.y ^ tg) | (w.z ^ tg) | (w.w ^ tg)) & 3u) == 0;
                if (__all_sync(0xffffffffu, ok)) break;
                if (!ok) w = ld_relaxed_v4(src);
                if (spins > SPIN_LIMIT_ITERS) __trap();
            }
            float v0 = __uint_as_float(w.x & ~3u), v1 = __uint_as_float(w.y & ~3u);
            float v2 = __uint_as_float(w.z & ~3u), v3 = __uint_as_float(w.w & ~3u);
            const bool u16 = lane & 16, u8 = lane & 8;
            float a0 = (u16 ? v2 : v0) + __shfl_xor_sync(0xffffffffu, u16 ? v0 : v2, 16);
            float a1 = (u16 ? v3 : v1) + __shfl_xor_sync(0xffffffffu, u16 ? v1 : v3, 16);
            float a = (u8 ? a1 : a0) + __shfl_xor_sync(0xffffffffu, u8 ? a0 : a1, 8);
            a += __shfl_xor_sync(0xffffffffu, a, 4);
            float* fin = reinterpret_cast<float*>(smem + OFF_FIN);
            if (!(lane & 4)) fin[warp * 16 + 4 * (lane & 3) + (u16 ? 2 : 0) + (u8 ? 1 : 0)] = a;
            if (warp != 0) {
                __syncwarp();
                named_arrive(6, 128);
            } else {
                named_sync(6, 128);
                if (lane < 16) {
                    const float sum = (fin[lane] + fin[16 + lane]) + (fin[32 + lane] + fin[48 + lane]);
                    out[b * DM + h * 16 + col] = __float2bfloat16_rn(x_v + bf16r(bf16r(sum) * gate_v));
                }
            }
        }
        return;
    }

    const int hw = warp - 4;
    if (hw >= 4) {
        const int i = tid - 256;
        if (i < 86) {
            prefetch_line(reinterpret_cast<const char*>(w1) + ((size_t)a_idx * 86 + i) * 128);
            prefetch_line(reinterpret_cast<const char*>(w2) + ((size_t)a_idx * 86 + i) * 128);
        }
        prefetch_line(reinterpret_cast<const char*>(wo) + ((size_t)a_idx * 256 + i) * 128);
        prefetch_line(reinterpret_cast<const char*>(wo) + ((size_t)a_idx * 256 + 128 + i) * 128);
    }
    cluster_arrive_relaxed();
    const uint32_t tag = ld_epoch(late(epoch_) + blockIdx.x) + 1;
    cluster_wait();
    if (hw < 4) {
        const uint32_t abase = sbase + OFF_WQ + (uint32_t)((mi >> 1) * 8 + r) * 128 + (uint32_t)(((2 * hw + (mi & 1)) ^ r) << 4);
        const uint4* xs = reinterpret_cast<const uint4*>(smem + OFF_XS + ((g & 1) * 4 + t) * (68 * 4));
        float qa[4][4];
#pragma unroll
        for (int i = 0; i < 4; i++) { qa[i][0] = 0.f; qa[i][1] = 0.f; qa[i][2] = 0.f; qa[i][3] = 0.f; }
        named_sync(1, 192);
#pragma unroll
        for (int half = 0; half < 2; half++) {
            uint32_t xw[32];
#pragma unroll
            for (int i = 0; i < 8; i++) {
                const uint4 v = xs[half * 8 + i];
                xw[4 * i] = v.x; xw[4 * i + 1] = v.y; xw[4 * i + 2] = v.z; xw[4 * i + 3] = v.w;
            }
            mbar_wait(bar_wq + 8 * half, 0);
#pragma unroll
            for (int ks = 0; ks < 16; ks++) {
                uint32_t a[4];
                ldsm4t(a, abase + (half * 16 + ks) * 2048);
                mma16816(qa[ks & 3], a[0], a[1], a[2], a[3], xw[2 * ks], xw[2 * ks + 1]);
            }
        }
        const int ci = t;
        float v = 0.f;
#pragma unroll
        for (int i = 0; i < 4; i++) v = (ci == i) ? ((qa[0][i] + qa[1][i]) + (qa[2][i] + qa[3][i])) : v;
        const float vo = __shfl_xor_sync(0xffffffffu, v, 4);
        if (!(g & 1)) {
            const uint32_t dst = t & 1;
            const uint32_t word = (uint32_t)(rank * 32 + hw * 8 + (t >> 1) * 4 + (g >> 1));
            st_async_u32(mapa(sbase + OFF_QBF + word * 4, dst), pack_bf16(v, vo), mapa(bar_q, dst));
        }
        asm volatile("fence.proxy.async.shared::cta;" ::: "memory");
        __syncwarp();
        if (lane == 0) mbar_arrive(bar_scr);
    }
    if (hw == 0) {
        const int gg = lane & 7, f = lane >> 3;
        const Word2 w = poll_word2(fxp + ((f * NB + b) * 32 + h) * 8 + gg, tag, 500);
        float s0 = __uint_as_float((uint32_t)w.a), s1 = __uint_as_float((uint32_t)w.b);
        s0 += __shfl_xor_sync(0xffffffffu, s0, 8);  s1 += __shfl_xor_sync(0xffffffffu, s1, 8);
        s0 += __shfl_xor_sync(0xffffffffu, s0, 16); s1 += __shfl_xor_sync(0xffffffffu, s1, 16);
        if (lane < 8) {
            float* gate = reinterpret_cast<float*>(smem + OFF_GATE);
            gate[gg] = bf16r(silu_f(bf16r(s0)));
            gate[gg + 8] = bf16r(silu_f(bf16r(s1)));
            gate[16 + gg] = __bfloat162float(x[b * DM + h * 16 + gg]);
            gate[24 + gg] = __bfloat162float(x[b * DM + h * 16 + gg + 8]);
        }
        __syncwarp();
        named_arrive(5, 64);
    }

    {
        const uint32_t base = sbase + OFF_WO + hw * 2048 + (uint32_t)((mi >> 1) * 8 + r) * 128;
        const uint32_t xo = (uint32_t)((mi & 1) ^ r) << 4;
        const uint4* obp = reinterpret_cast<const uint4*>(ob + (g & 3) * 80 + t * 20);
        const int sdst = (t & 1) * 2 + (t >> 1);
        uint2* dst = reinterpret_cast<uint2*>(oxp + ((b * 32 + 4 * hw + sdst) * NH + h) * 4) + g;
        mbar_wait(bar_wo, 0);
        {
            uint32_t wf[7][4][4];
#pragma unroll
            for (int kk = 0; kk < 7; kk++)
#pragma unroll
                for (int s = 0; s < 4; s++) ldsm4t(wf[kk][s], base + kk * WO_PIECE_BYTES + (xo ^ (s << 5)));
            st_relaxed_v2(dst, (tag - 1) & 3, (tag - 1) & 3);
            named_sync(4, 384);
            float pacc[4][4];
#pragma unroll
            for (int s = 0; s < 4; s++) { pacc[s][0] = 0.f; pacc[s][1] = 0.f; pacc[s][2] = 0.f; pacc[s][3] = 0.f; }
            uint4 ow = obp[0];
#pragma unroll
            for (int s = 0; s < 4; s++) mma16816(pacc[s], wf[0][s][0], wf[0][s][1], wf[0][s][2], wf[0][s][3], ow.x, ow.y);
#pragma unroll
            for (int s = 0; s < 4; s++) mma16816(pacc[s], wf[1][s][0], wf[1][s][1], wf[1][s][2], wf[1][s][3], ow.z, ow.w);
#pragma unroll
            for (int i = 1; i < 3; i++) {
                ow = obp[i];
#pragma unroll
                for (int s = 0; s < 4; s++)
                    mma16816(pacc[s], wf[2 * i][s][0], wf[2 * i][s][1], wf[2 * i][s][2], wf[2 * i][s][3], ow.x, ow.y);
#pragma unroll
                for (int s = 0; s < 4; s++)
                    mma16816(pacc[s], wf[2 * i + 1][s][0], wf[2 * i + 1][s][1], wf[2 * i + 1][s][2], wf[2 * i + 1][s][3], ow.z, ow.w);
            }
            ow = obp[3];
#pragma unroll
            for (int s = 0; s < 4; s++) mma16816(pacc[s], wf[6][s][0], wf[6][s][1], wf[6][s][2], wf[6][s][3], ow.x, ow.y);
#pragma unroll
            for (int s = 0; s < 4; s++) {
                uint32_t w7[4];
                ldsm4t(w7, base + 7 * WO_PIECE_BYTES + (xo ^ (s << 5)));
                mma16816(pacc[s], w7[0], w7[1], w7[2], w7[3], ow.z, ow.w);
            }
            float v0[4], v1[4];
#pragma unroll
            for (int s = 0; s < 4; s++) { v0[s] = pacc[s][0] + pacc[s][1]; v1[s] = pacc[s][2] + pacc[s][3]; }
            const bool to = t & 1, th = t >> 1;
            const float ka0 = to ? v0[2] : v0[0], ka1 = to ? v0[3] : v0[1], kb0 = to ? v1[2] : v1[0], kb1 = to ? v1[3] : v1[1];
            const float sa0 = to ? v0[0] : v0[2], sa1 = to ? v0[1] : v0[3], sb0 = to ? v1[0] : v1[2], sb1 = to ? v1[1] : v1[3];
            const float sa = th ? sa1 : sa0, sb = th ? sb1 : sb0;
            const float ra = __shfl_xor_sync(0xffffffffu, sa, 1), rb = __shfl_xor_sync(0xffffffffu, sb, 1);
            const float o0 = (th ? ka1 : ka0) + ra, o1 = (th ? kb1 : kb0) + rb;
            const uint32_t tg = tag & 3;
            st_relaxed_v2(dst, (__float_as_uint(o0) & ~3u) | tg, (__float_as_uint(o1) & ~3u) | tg);
        }
    }
}

}

extern "C" void kernel_launch(void* const* d_in, const int* in_sizes, int n_in, void* d_out, int out_size) {
    (void)in_sizes; (void)n_in; (void)out_size;
    const __nv_bfloat16* x = (const __nv_bfloat16*)d_in[0];
    const __nv_bfloat16* kc = (const __nv_bfloat16*)d_in[1];
    const __nv_bfloat16* vc = (const __nv_bfloat16*)d_in[2];
    const __nv_bfloat16* wq = (const __nv_bfloat16*)d_in[3];
    const __nv_bfloat16* wo = (const __nv_bfloat16*)d_in[4];
    const __nv_bfloat16* w1 = (const __nv_bfloat16*)d_in[6];
    const __nv_bfloat16* w2 = (const __nv_bfloat16*)d_in[7];
    typedef CUresult (*EncodeFn)(CUtensorMap*, CUtensorMapDataType, cuuint32_t, void*, const cuuint64_t*, const cuuint64_t*,
                                 const cuuint32_t*, const cuuint32_t*, CUtensorMapInterleave, CUtensorMapSwizzle,
                                 CUtensorMapL2promotion, CUtensorMapFloatOOBfill);
    static unsigned int *epoch = nullptr, *progp = nullptr;
    static uint4* oxp = nullptr;
    static Word2* fxp = nullptr;
    static EncodeFn encode = nullptr;
    if (!epoch) {
        cudaFuncSetAttribute(fused_decode_kernel, cudaFuncAttributeMaxDynamicSharedMemorySize, SMEM_BYTES);
        void* fn = nullptr;
        cudaDriverEntryPointQueryResult qr;
        cudaGetDriverEntryPoint("cuTensorMapEncodeTiled", &fn, cudaEnableDefault, &qr);
        encode = (EncodeFn)fn;
        cudaGetSymbolAddress((void**)&oxp, g_ox);
        cudaGetSymbolAddress((void**)&fxp, g_fx);
        cudaGetSymbolAddress((void**)&progp, g_prog);
        cudaGetSymbolAddress((void**)&epoch, g_epoch);
    }
    CUtensorMap wq_map, wo_map;
    const cuuint32_t estride[2] = {1, 1};
    {
        const cuuint64_t gdim[2] = {(cuuint64_t)(NH * DH), (cuuint64_t)DM}, gstride[1] = {(cuuint64_t)(NH * DH * 2)};
        const cuuint32_t box[2] = {64, 256};
        encode(&wq_map, CU_TENSOR_MAP_DATA_TYPE_BFLOAT16, 2, (void*)wq, gdim, gstride, box, estride, CU_TENSOR_MAP_INTERLEAVE_NONE,
               CU_TENSOR_MAP_SWIZZLE_128B, CU_TENSOR_MAP_L2_PROMOTION_NONE, CU_TENSOR_MAP_FLOAT_OOB_FILL_NONE);
    }
    {
        const cuuint64_t gdim[3] = {64, (cuuint64_t)(NH * DH), 8}, gstride[2] = {(cuuint64_t)(DM * 2), 128};
        const cuuint32_t box[3] = {64, 16, 8}, es3[3] = {1, 1, 1};
        encode(&wo_map, CU_TENSOR_MAP_DATA_TYPE_BFLOAT16, 3, (void*)wo, gdim, gstride, box, es3, CU_TENSOR_MAP_INTERLEAVE_NONE,
               CU_TENSOR_MAP_SWIZZLE_128B, CU_TENSOR_MAP_L2_PROMOTION_NONE, CU_TENSOR_MAP_FLOAT_OOB_FILL_NONE);
    }
    fused_decode_kernel<<<NCTA, NTHREADS, SMEM_BYTES, cudaStreamPerThread>>>(x, kc, vc, (__nv_bfloat16*)d_out, w1, w2, wo,
                                                                             epoch, progp, oxp, fxp, wq_map, wo_map);
}
```
